```python
import torch

def _softmax(x, axis=-1):
    return torch.softmax(x, dim=axis)
def _gelu(x):
    return torch.nn.functional.gelu(x, approximate="tanh")
def _silu(x):
    return torch.nn.functional.silu(x)
def _sigmoid(x):
    return torch.sigmoid(x)
def _layernorm(x, axis=-1, eps=1e-5):
    m = x.mean(dim=axis, keepdim=True)
    v = x.var(dim=axis, keepdim=True, unbiased=False)
    return (x - m) / torch.sqrt(v + eps)
def _scatter_add(tgt, idx, src, axis=0):
    return tgt.clone().index_add_(axis, idx, src)
def _segment_sum(src, seg, n):
    out = torch.zeros((n,) + src.shape[1:], dtype=src.dtype)
    return out.index_add_(0, seg, src)
def _pad(x, pw):
    flat = tuple(v for pair in reversed(pw) for v in pair)
    return torch.nn.functional.pad(x, flat)

kernel_name = 'sequential_preLN__grouped_kv_mqa__moe_arch_mod__prompt'

def setup_inputs():

    _w = (lambda a: (lambda t: t.to(torch.bfloat16) if t.is_floating_point() else t)(torch.as_tensor(a)))
    def _A_setup():
        B, S, D, H = 1, 2048, 576, 32
        Dh = D // H
        return {
            "x": _w((lambda *s: torch.randn(*s, dtype=torch.bfloat16) * 0.05)(B, S, D)),
            "wq": _w((lambda *s: torch.randn(*s, dtype=torch.bfloat16) * 0.05)(D, H * Dh)),
            "wk": _w((lambda *s: torch.randn(*s, dtype=torch.bfloat16) * 0.05)(D, Dh)),
            "wv": _w((lambda *s: torch.randn(*s, dtype=torch.bfloat16) * 0.05)(D, Dh)),
            "wo": _w((lambda *s: torch.randn(*s, dtype=torch.bfloat16) * 0.05)(H * Dh, D)),
        }
    _A_in = _A_setup()

    def _B_setup():
        B, S, D, F, C = 1, 2048, 576, 4608, 8
        return {
            "x": _w((lambda *s: torch.randn(*s, dtype=torch.bfloat16) * 0.05)(B, S, D)),
            "w_r": _w((lambda *s: torch.randn(*s, dtype=torch.bfloat16) * 0.05)(D)),
            "w_gate": _w((lambda *s: torch.randn(*s, dtype=torch.bfloat16) * 0.05)(D, F)),
            "w_up": _w((lambda *s: torch.randn(*s, dtype=torch.bfloat16) * 0.05)(D, F)),
            "w_down": _w((lambda *s: torch.randn(*s, dtype=torch.bfloat16) * 0.05)(F, D)),
        }
    _B_in = _B_setup()

    return {
        "A_x": _A_in["x"],
        "A_wq": _A_in["wq"],
        "A_wk": _A_in["wk"],
        "A_wv": _A_in["wv"],
        "A_wo": _A_in["wo"],
        "B_x": _B_in["x"],
        "B_w_r": _B_in["w_r"],
        "B_w_gate": _B_in["w_gate"],
        "B_w_up": _B_in["w_up"],
        "B_w_down": _B_in["w_down"],
    }

def reference(A_x, A_wq, A_wk, A_wv, A_wo, B_x, B_w_r, B_w_gate, B_w_up, B_w_down):
    def _A_ref(x, wq, wk, wv, wo):
        B, S, D = x.shape
        H = 32
        Dh = D // H
        q = (lambda x, *d: x.permute(*d))((x @ wq).reshape(B, S, H, Dh), 0, 2, 1, 3)
        k = x @ wk
        v = x @ wv
        scores = torch.einsum("bhqd,bkd->bhqk", q, k) * (Dh ** -0.5)
        p = _softmax(scores, axis=-1)
        o = torch.einsum("bhqk,bkd->bhqd", p, v)
        return (lambda x, *d: x.permute(*d))(o, 0, 2, 1, 3).reshape(B, S, H * Dh) @ wo

    def _B_ref(x, w_r, w_gate, w_up, w_down):
        B, S, D = x.shape
        C = 8
        r = x @ w_r
        idx = torch.argsort(-r, axis=-1)[:, :C]
        idx_e = (lambda x, n, axis: torch.repeat_interleave(x, n, dim=axis))(idx.reshape(B, C, 1), D, axis=2)
        x_sel = (lambda x, i, axis: torch.take_along_dim(x, i, dim=axis))(x, idx_e, axis=1)
        g = _silu(x_sel @ w_gate)
        u = x_sel @ w_up
        y = (g * u) @ w_down
        r_sel = _sigmoid((lambda x, i, axis: torch.take_along_dim(x, i, dim=axis))(r, idx, axis=1))
        y = y * r_sel.reshape(B, C, 1)
        b_off = (torch.arange(B) * S).reshape(B, 1)
        flat_idx = (idx + b_off).reshape(B * C)
        zero = (x * 0.0).reshape(B * S, D)
        upd = _scatter_add(zero, flat_idx, y.reshape(B * C, D), axis=0)
        return x + upd.reshape(B, S, D)

    x = A_x
    h = x + _A_ref(_layernorm(x, axis=-1), A_wq, A_wk, A_wv, A_wo)
    h2 = h + _B_ref(_layernorm(h, axis=-1), B_w_r, B_w_gate, B_w_up, B_w_down)
    return h2
```

```cpp
#include <cuda_runtime.h>
#include <cuda_bf16.h>
#include <cuda_fp16.h>
#include <cuda.h>
#include <stdint.h>

#define POLY_DEG3 1

__device__ __forceinline__ void wgz_rs_n256_f16_f16(uint32_t* d, uint32_t a0, uint32_t a1, uint32_t a2, uint32_t a3, uint64_t db) {
  asm volatile("{\n.reg .pred p;\nsetp.ne.b32 p, 0, 0;\n"
    "wgmma.mma_async.sync.aligned.m64n256k16.f16.f16.f16 "
    "{%0,%1,%2,%3,%4,%5,%6,%7,%8,%9,%10,%11,%12,%13,%14,%15,%16,%17,%18,%19,%20,%21,%22,%23,%24,%25,%26,%27,%28,%29,%30,%31,%32,%33,%34,%35,%36,%37,%38,%39,%40,%41,%42,%43,%44,%45,%46,%47,%48,%49,%50,%51,%52,%53,%54,%55,%56,%57,%58,%59,%60,%61,%62,%63}, "
    "{%64,%65,%66,%67}, %68, p, 1, 1, 0;\n}\n"
    : "=r"(d[0]), "=r"(d[1]), "=r"(d[2]), "=r"(d[3]), "=r"(d[4]), "=r"(d[5]), "=r"(d[6]), "=r"(d[7]),
      "=r"(d[8]), "=r"(d[9]), "=r"(d[10]), "=r"(d[11]), "=r"(d[12]), "=r"(d[13]), "=r"(d[14]), "=r"(d[15]),
      "=r"(d[16]), "=r"(d[17]), "=r"(d[18]), "=r"(d[19]), "=r"(d[20]), "=r"(d[21]), "=r"(d[22]), "=r"(d[23]),
      "=r"(d[24]), "=r"(d[25]), "=r"(d[26]), "=r"(d[27]), "=r"(d[28]), "=r"(d[29]), "=r"(d[30]), "=r"(d[31]),
      "=r"(d[32]), "=r"(d[33]), "=r"(d[34]), "=r"(d[35]), "=r"(d[36]), "=r"(d[37]), "=r"(d[38]), "=r"(d[39]),
      "=r"(d[40]), "=r"(d[41]), "=r"(d[42]), "=r"(d[43]), "=r"(d[44]), "=r"(d[45]), "=r"(d[46]), "=r"(d[47]),
      "=r"(d[48]), "=r"(d[49]), "=r"(d[50]), "=r"(d[51]), "=r"(d[52]), "=r"(d[53]), "=r"(d[54]), "=r"(d[55]),
      "=r"(d[56]), "=r"(d[57]), "=r"(d[58]), "=r"(d[59]), "=r"(d[60]), "=r"(d[61]), "=r"(d[62]), "=r"(d[63])
    : "r"(a0), "r"(a1), "r"(a2), "r"(a3), "l"(db));
}
__device__ __forceinline__ void wg_rs_n256_f16_f16(uint32_t* d, uint32_t a0, uint32_t a1, uint32_t a2, uint32_t a3, uint64_t db) {
  asm volatile("{\n.reg .pred p;\nsetp.ne.b32 p, 1, 0;\n"
    "wgmma.mma_async.sync.aligned.m64n256k16.f16.f16.f16 "
    "{%0,%1,%2,%3,%4,%5,%6,%7,%8,%9,%10,%11,%12,%13,%14,%15,%16,%17,%18,%19,%20,%21,%22,%23,%24,%25,%26,%27,%28,%29,%30,%31,%32,%33,%34,%35,%36,%37,%38,%39,%40,%41,%42,%43,%44,%45,%46,%47,%48,%49,%50,%51,%52,%53,%54,%55,%56,%57,%58,%59,%60,%61,%62,%63}, "
    "{%64,%65,%66,%67}, %68, p, 1, 1, 0;\n}\n"
    : "+r"(d[0]), "+r"(d[1]), "+r"(d[2]), "+r"(d[3]), "+r"(d[4]), "+r"(d[5]), "+r"(d[6]), "+r"(d[7]),
      "+r"(d[8]), "+r"(d[9]), "+r"(d[10]), "+r"(d[11]), "+r"(d[12]), "+r"(d[13]), "+r"(d[14]), "+r"(d[15]),
      "+r"(d[16]), "+r"(d[17]), "+r"(d[18]), "+r"(d[19]), "+r"(d[20]), "+r"(d[21]), "+r"(d[22]), "+r"(d[23]),
      "+r"(d[24]), "+r"(d[25]), "+r"(d[26]), "+r"(d[27]), "+r"(d[28]), "+r"(d[29]), "+r"(d[30]), "+r"(d[31]),
      "+r"(d[32]), "+r"(d[33]), "+r"(d[34]), "+r"(d[35]), "+r"(d[36]), "+r"(d[37]), "+r"(d[38]), "+r"(d[39]),
      "+r"(d[40]), "+r"(d[41]), "+r"(d[42]), "+r"(d[43]), "+r"(d[44]), "+r"(d[45]), "+r"(d[46]), "+r"(d[47]),
      "+r"(d[48]), "+r"(d[49]), "+r"(d[50]), "+r"(d[51]), "+r"(d[52]), "+r"(d[53]), "+r"(d[54]), "+r"(d[55]),
      "+r"(d[56]), "+r"(d[57]), "+r"(d[58]), "+r"(d[59]), "+r"(d[60]), "+r"(d[61]), "+r"(d[62]), "+r"(d[63])
    : "r"(a0), "r"(a1), "r"(a2), "r"(a3), "l"(db));
}
__device__ __forceinline__ void wg_rs_n24_f32_f16(float* d, uint32_t a0, uint32_t a1, uint32_t a2, uint32_t a3, uint64_t db) {
  asm volatile("{\n.reg .pred p;\nsetp.ne.b32 p, 1, 0;\n"
    "wgmma.mma_async.sync.aligned.m64n24k16.f32.f16.f16 "
    "{%0,%1,%2,%3,%4,%5,%6,%7,%8,%9,%10,%11}, "
    "{%12,%13,%14,%15}, %16, p, 1, 1, 1;\n}\n"
    : "+f"(d[0]), "+f"(d[1]), "+f"(d[2]), "+f"(d[3]), "+f"(d[4]), "+f"(d[5]), "+f"(d[6]), "+f"(d[7]),
      "+f"(d[8]), "+f"(d[9]), "+f"(d[10]), "+f"(d[11])
    : "r"(a0), "r"(a1), "r"(a2), "r"(a3), "l"(db));
}
__device__ __forceinline__ void wgz_ss_n128_f32_bf16(float* d, uint64_t da, uint64_t db) {
  asm volatile("{\n.reg .pred p;\nsetp.ne.b32 p, 0, 0;\n"
    "wgmma.mma_async.sync.aligned.m64n128k16.f32.bf16.bf16 "
    "{%0,%1,%2,%3,%4,%5,%6,%7,%8,%9,%10,%11,%12,%13,%14,%15,%16,%17,%18,%19,%20,%21,%22,%23,%24,%25,%26,%27,%28,%29,%30,%31,%32,%33,%34,%35,%36,%37,%38,%39,%40,%41,%42,%43,%44,%45,%46,%47,%48,%49,%50,%51,%52,%53,%54,%55,%56,%57,%58,%59,%60,%61,%62,%63}, "
    "%64, %65, p, 1, 1, 0, 1;\n}\n"
    : "=f"(d[0]), "=f"(d[1]), "=f"(d[2]), "=f"(d[3]), "=f"(d[4]), "=f"(d[5]), "=f"(d[6]), "=f"(d[7]),
      "=f"(d[8]), "=f"(d[9]), "=f"(d[10]), "=f"(d[11]), "=f"(d[12]), "=f"(d[13]), "=f"(d[14]), "=f"(d[15]),
      "=f"(d[16]), "=f"(d[17]), "=f"(d[18]), "=f"(d[19]), "=f"(d[20]), "=f"(d[21]), "=f"(d[22]), "=f"(d[23]),
      "=f"(d[24]), "=f"(d[25]), "=f"(d[26]), "=f"(d[27]), "=f"(d[28]), "=f"(d[29]), "=f"(d[30]), "=f"(d[31]),
      "=f"(d[32]), "=f"(d[33]), "=f"(d[34]), "=f"(d[35]), "=f"(d[36]), "=f"(d[37]), "=f"(d[38]), "=f"(d[39]),
      "=f"(d[40]), "=f"(d[41]), "=f"(d[42]), "=f"(d[43]), "=f"(d[44]), "=f"(d[45]), "=f"(d[46]), "=f"(d[47]),
      "=f"(d[48]), "=f"(d[49]), "=f"(d[50]), "=f"(d[51]), "=f"(d[52]), "=f"(d[53]), "=f"(d[54]), "=f"(d[55]),
      "=f"(d[56]), "=f"(d[57]), "=f"(d[58]), "=f"(d[59]), "=f"(d[60]), "=f"(d[61]), "=f"(d[62]), "=f"(d[63])
    : "l"(da), "l"(db));
}
__device__ __forceinline__ void wg_ss_n128_f32_bf16(float* d, uint64_t da, uint64_t db) {
  asm volatile("{\n.reg .pred p;\nsetp.ne.b32 p, 1, 0;\n"
    "wgmma.mma_async.sync.aligned.m64n128k16.f32.bf16.bf16 "
    "{%0,%1,%2,%3,%4,%5,%6,%7,%8,%9,%10,%11,%12,%13,%14,%15,%16,%17,%18,%19,%20,%21,%22,%23,%24,%25,%26,%27,%28,%29,%30,%31,%32,%33,%34,%35,%36,%37,%38,%39,%40,%41,%42,%43,%44,%45,%46,%47,%48,%49,%50,%51,%52,%53,%54,%55,%56,%57,%58,%59,%60,%61,%62,%63}, "
    "%64, %65, p, 1, 1, 0, 1;\n}\n"
    : "+f"(d[0]), "+f"(d[1]), "+f"(d[2]), "+f"(d[3]), "+f"(d[4]), "+f"(d[5]), "+f"(d[6]), "+f"(d[7]),
      "+f"(d[8]), "+f"(d[9]), "+f"(d[10]), "+f"(d[11]), "+f"(d[12]), "+f"(d[13]), "+f"(d[14]), "+f"(d[15]),
      "+f"(d[16]), "+f"(d[17]), "+f"(d[18]), "+f"(d[19]), "+f"(d[20]), "+f"(d[21]), "+f"(d[22]), "+f"(d[23]),
      "+f"(d[24]), "+f"(d[25]), "+f"(d[26]), "+f"(d[27]), "+f"(d[28]), "+f"(d[29]), "+f"(d[30]), "+f"(d[31]),
      "+f"(d[32]), "+f"(d[33]), "+f"(d[34]), "+f"(d[35]), "+f"(d[36]), "+f"(d[37]), "+f"(d[38]), "+f"(d[39]),
      "+f"(d[40]), "+f"(d[41]), "+f"(d[42]), "+f"(d[43]), "+f"(d[44]), "+f"(d[45]), "+f"(d[46]), "+f"(d[47]),
      "+f"(d[48]), "+f"(d[49]), "+f"(d[50]), "+f"(d[51]), "+f"(d[52]), "+f"(d[53]), "+f"(d[54]), "+f"(d[55]),
      "+f"(d[56]), "+f"(d[57]), "+f"(d[58]), "+f"(d[59]), "+f"(d[60]), "+f"(d[61]), "+f"(d[62]), "+f"(d[63])
    : "l"(da), "l"(db));
}
__device__ __forceinline__ void wgz_ss_n16_f32_bf16(float* d, uint64_t da, uint64_t db) {
  asm volatile("{\n.reg .pred p;\nsetp.ne.b32 p, 0, 0;\n"
    "wgmma.mma_async.sync.aligned.m64n16k16.f32.bf16.bf16 "
    "{%0,%1,%2,%3,%4,%5,%6,%7}, "
    "%8, %9, p, 1, 1, 0, 1;\n}\n"
    : "=f"(d[0]), "=f"(d[1]), "=f"(d[2]), "=f"(d[3]), "=f"(d[4]), "=f"(d[5]), "=f"(d[6]), "=f"(d[7])
    : "l"(da), "l"(db));
}
__device__ __forceinline__ void wg_ss_n16_f32_bf16(float* d, uint64_t da, uint64_t db) {
  asm volatile("{\n.reg .pred p;\nsetp.ne.b32 p, 1, 0;\n"
    "wgmma.mma_async.sync.aligned.m64n16k16.f32.bf16.bf16 "
    "{%0,%1,%2,%3,%4,%5,%6,%7}, "
    "%8, %9, p, 1, 1, 0, 1;\n}\n"
    : "+f"(d[0]), "+f"(d[1]), "+f"(d[2]), "+f"(d[3]), "+f"(d[4]), "+f"(d[5]), "+f"(d[6]), "+f"(d[7])
    : "l"(da), "l"(db));
}
__device__ __forceinline__ void wgz_ss_n144_f32_bf16(float* d, uint64_t da, uint64_t db) {
  asm volatile("{\n.reg .pred p;\nsetp.ne.b32 p, 0, 0;\n"
    "wgmma.mma_async.sync.aligned.m64n144k16.f32.bf16.bf16 "
    "{%0,%1,%2,%3,%4,%5,%6,%7,%8,%9,%10,%11,%12,%13,%14,%15,%16,%17,%18,%19,%20,%21,%22,%23,%24,%25,%26,%27,%28,%29,%30,%31,%32,%33,%34,%35,%36,%37,%38,%39,%40,%41,%42,%43,%44,%45,%46,%47,%48,%49,%50,%51,%52,%53,%54,%55,%56,%57,%58,%59,%60,%61,%62,%63,%64,%65,%66,%67,%68,%69,%70,%71}, "
    "%72, %73, p, 1, 1, 0, 1;\n}\n"
    : "=f"(d[0]), "=f"(d[1]), "=f"(d[2]), "=f"(d[3]), "=f"(d[4]), "=f"(d[5]), "=f"(d[6]), "=f"(d[7]),
      "=f"(d[8]), "=f"(d[9]), "=f"(d[10]), "=f"(d[11]), "=f"(d[12]), "=f"(d[13]), "=f"(d[14]), "=f"(d[15]),
      "=f"(d[16]), "=f"(d[17]), "=f"(d[18]), "=f"(d[19]), "=f"(d[20]), "=f"(d[21]), "=f"(d[22]), "=f"(d[23]),
      "=f"(d[24]), "=f"(d[25]), "=f"(d[26]), "=f"(d[27]), "=f"(d[28]), "=f"(d[29]), "=f"(d[30]), "=f"(d[31]),
      "=f"(d[32]), "=f"(d[33]), "=f"(d[34]), "=f"(d[35]), "=f"(d[36]), "=f"(d[37]), "=f"(d[38]), "=f"(d[39]),
      "=f"(d[40]), "=f"(d[41]), "=f"(d[42]), "=f"(d[43]), "=f"(d[44]), "=f"(d[45]), "=f"(d[46]), "=f"(d[47]),
      "=f"(d[48]), "=f"(d[49]), "=f"(d[50]), "=f"(d[51]), "=f"(d[52]), "=f"(d[53]), "=f"(d[54]), "=f"(d[55]),
      "=f"(d[56]), "=f"(d[57]), "=f"(d[58]), "=f"(d[59]), "=f"(d[60]), "=f"(d[61]), "=f"(d[62]), "=f"(d[63]),
      "=f"(d[64]), "=f"(d[65]), "=f"(d[66]), "=f"(d[67]), "=f"(d[68]), "=f"(d[69]), "=f"(d[70]), "=f"(d[71])
    : "l"(da), "l"(db));
}
__device__ __forceinline__ void wg_ss_n144_f32_bf16(float* d, uint64_t da, uint64_t db) {
  asm volatile("{\n.reg .pred p;\nsetp.ne.b32 p, 1, 0;\n"
    "wgmma.mma_async.sync.aligned.m64n144k16.f32.bf16.bf16 "
    "{%0,%1,%2,%3,%4,%5,%6,%7,%8,%9,%10,%11,%12,%13,%14,%15,%16,%17,%18,%19,%20,%21,%22,%23,%24,%25,%26,%27,%28,%29,%30,%31,%32,%33,%34,%35,%36,%37,%38,%39,%40,%41,%42,%43,%44,%45,%46,%47,%48,%49,%50,%51,%52,%53,%54,%55,%56,%57,%58,%59,%60,%61,%62,%63,%64,%65,%66,%67,%68,%69,%70,%71}, "
    "%72, %73, p, 1, 1, 0, 1;\n}\n"
    : "+f"(d[0]), "+f"(d[1]), "+f"(d[2]), "+f"(d[3]), "+f"(d[4]), "+f"(d[5]), "+f"(d[6]), "+f"(d[7]),
      "+f"(d[8]), "+f"(d[9]), "+f"(d[10]), "+f"(d[11]), "+f"(d[12]), "+f"(d[13]), "+f"(d[14]), "+f"(d[15]),
      "+f"(d[16]), "+f"(d[17]), "+f"(d[18]), "+f"(d[19]), "+f"(d[20]), "+f"(d[21]), "+f"(d[22]), "+f"(d[23]),
      "+f"(d[24]), "+f"(d[25]), "+f"(d[26]), "+f"(d[27]), "+f"(d[28]), "+f"(d[29]), "+f"(d[30]), "+f"(d[31]),
      "+f"(d[32]), "+f"(d[33]), "+f"(d[34]), "+f"(d[35]), "+f"(d[36]), "+f"(d[37]), "+f"(d[38]), "+f"(d[39]),
      "+f"(d[40]), "+f"(d[41]), "+f"(d[42]), "+f"(d[43]), "+f"(d[44]), "+f"(d[45]), "+f"(d[46]), "+f"(d[47]),
      "+f"(d[48]), "+f"(d[49]), "+f"(d[50]), "+f"(d[51]), "+f"(d[52]), "+f"(d[53]), "+f"(d[54]), "+f"(d[55]),
      "+f"(d[56]), "+f"(d[57]), "+f"(d[58]), "+f"(d[59]), "+f"(d[60]), "+f"(d[61]), "+f"(d[62]), "+f"(d[63]),
      "+f"(d[64]), "+f"(d[65]), "+f"(d[66]), "+f"(d[67]), "+f"(d[68]), "+f"(d[69]), "+f"(d[70]), "+f"(d[71])
    : "l"(da), "l"(db));
}

typedef __nv_bfloat16 bf16;
constexpr int SEQ = 2048, DM = 576, FF = 4608;
constexpr int NCTA = 128, NTHR = 512;

struct LLScratch {
    uint32_t o[32][8][2304];
    uint32_t h[SEQ][288];
    float    y[72][NCTA][64];
    float4   part[32][4][64];
    float2   stat2[SEQ];
    uint32_t rkey[SEQ];
};
static_assert(sizeof(LLScratch) % (NCTA * 16) == 0, "zero slices");
__device__ __align__(1024) LLScratch g_ll;
__device__ __align__(1024) uint4 g_kv[SEQ * 5];
__device__ __align__(1024) uint4 g_wo[4 * 36 * 288];
__device__ __align__(128) float4 g_kvraw[SEQ * 9];
__device__ __align__(128) float4 g_info[NCTA];
__device__ __align__(128) float2 g_stat1[SEQ];
__device__ __align__(128) float  g_colsum[4][DM];
__device__ __align__(128) uint32_t g_cnt[64];
constexpr uint32_t CNT1 = NCTA + 72 * 4, CNT2 = NCTA;

#define TS(i)

constexpr int SM_WQ0 = 129024;
constexpr int SM_X = 147456;
constexpr int SM_OLO = 126976, SM_OHI = 163840;
constexpr int SM_A = 200704;
constexpr int SM_XS = 27648;
constexpr int SM_G0 = 50688, SM_U0 = 66048, SM_G1 = 163840, SM_U1 = 179200, SM_G2 = 82944, SM_U2 = 98304;
constexpr int SM_DN = 113664;
constexpr int SM_HN = SM_A, SM_HS = SM_A + 9344;
constexpr int SM_MISC = 221184;
constexpr int SM_BAR = SM_MISC + 10880;
constexpr int SM_TOTAL = 232448;
constexpr int MI_STAT = 0;
constexpr int MI_CS = 512;
constexpr int MI_KP = 1088;
constexpr int MI_WMAX = 1152;
constexpr int MI_NC = 1216;
constexpr int MI_SEL = 1232;
constexpr int MI_ACT = 1312;
constexpr int MI_RED = 2304;
enum { B_FULL = 0, B_QC = 9, B_KVF = 18, B_KVD = 26, B_AUX = 32, B_ZOK, B_QRD, B_WO0, B_WO1, B_OHI, B_OHT, B_OC, B_OM, B_OE, B_GU, B_DN, B_NUM };
static_assert(B_NUM * 8 <= SM_TOTAL - SM_BAR, "barriers");

#define WG_FENCE() asm volatile("wgmma.fence.sync.aligned;" ::: "memory")
#define WG_COMMIT() asm volatile("wgmma.commit_group.sync.aligned;" ::: "memory")
#define WG_WAIT(n) asm volatile("wgmma.wait_group.sync.aligned %0;" :: "n"(n) : "memory")
#define BAR_SYNC(id, n) asm volatile("barrier.cta.sync %0, %1;" :: "n"(id), "n"(n) : "memory")
#define BAR_ARRIVE(id, n) asm volatile("barrier.cta.arrive %0, %1;" :: "n"(id), "n"(n) : "memory")
#define PROXY_FENCE() asm volatile("fence.proxy.async;" ::: "memory")
#define PROXY_FENCE_SMEM() asm volatile("fence.proxy.async.shared::cta;" ::: "memory")

__device__ __forceinline__ uint64_t mkdesc(uint32_t addr, uint32_t lbo, uint32_t sbo, uint32_t mode) {
    return (uint64_t)((addr & 0x3FFFF) >> 4) | ((uint64_t)(lbo >> 4) << 16) | ((uint64_t)(sbo >> 4) << 32) | ((uint64_t)mode << 62);
}
__device__ __forceinline__ void mbar_init(uint32_t b, int c) { asm volatile("mbarrier.init.shared::cta.b64 [%0], %1;" :: "r"(b), "r"(c) : "memory"); }
__device__ __forceinline__ void mbar_expect(uint32_t b, uint32_t tx) { asm volatile("mbarrier.arrive.expect_tx.shared::cta.b64 _, [%0], %1;" :: "r"(b), "r"(tx) : "memory"); }
__device__ __forceinline__ void mbar_arrive(uint32_t b) { asm volatile("mbarrier.arrive.shared::cta.b64 _, [%0];" :: "r"(b) : "memory"); }
__device__ __forceinline__ bool mbar_try(uint32_t b) {
    uint32_t ok;
    asm volatile("{.reg .pred p; mbarrier.try_wait.parity.shared::cta.b64 p, [%1], 0; selp.u32 %0, 1, 0, p;}" : "=r"(ok) : "r"(b) : "memory");
    return ok;
}
__device__ __forceinline__ bool mbar_test(uint32_t b) {
    uint32_t ok;
    asm volatile("{.reg .pred p; mbarrier.test_wait.parity.shared::cta.b64 p, [%1], 0; selp.u32 %0, 1, 0, p;}" : "=r"(ok) : "r"(b) : "memory");
    return ok;
}
__device__ __forceinline__ void mbar_wait(uint32_t b) {
    if (mbar_try(b)) return;
    for (int i = 0; i < (1 << 22); i++) if (mbar_try(b)) return;
    __trap();
}
__device__ __forceinline__ void bulk_ld(uint32_t dst, const void* src, uint32_t bytes, uint32_t bar) {
    asm volatile("cp.async.bulk.shared::cluster.global.mbarrier::complete_tx::bytes [%0], [%1], %2, [%3];"
                 :: "r"(dst), "l"(src), "r"(bytes), "r"(bar) : "memory");
}
__device__ __forceinline__ void tma2d(uint32_t dst, const CUtensorMap* tm, int c0, int c1, uint32_t bar) {
    asm volatile("cp.async.bulk.tensor.2d.shared::cluster.global.mbarrier::complete_tx::bytes [%0], [%1, {%3, %4}], [%2];"
                 :: "r"(dst), "l"(tm), "r"(bar), "r"(c0), "r"(c1) : "memory");
}
__device__ __forceinline__ void l2_prefetch(const void* src, uint32_t bytes) {
    asm volatile("cp.async.bulk.prefetch.L2.global [%0], %1;" :: "l"(src), "r"(bytes) : "memory");
}
__device__ __forceinline__ void red_release(uint32_t* p) { asm volatile("red.release.gpu.global.add.u32 [%0], 1;" :: "l"(p) : "memory"); }
__device__ __forceinline__ void poll_counter(const uint32_t* p, uint32_t target) {
    for (int i = 0; i < (1 << 22); i++) {
        uint32_t v;
        asm volatile("ld.acquire.gpu.global.u32 %0, [%1];" : "=r"(v) : "l"(p) : "memory");
        if (v >= target) return;
        __nanosleep(20);
    }
    __trap();
}
__device__ __forceinline__ uint4 ld_rlx16(const void* p) {
    uint4 v;
    asm volatile("ld.relaxed.gpu.global.v4.u32 {%0,%1,%2,%3}, [%4];" : "=r"(v.x), "=r"(v.y), "=r"(v.z), "=r"(v.w) : "l"(p) : "memory");
    return v;
}
__device__ __forceinline__ uint2 ld_rlx8(const void* p) {
    uint2 v;
    asm volatile("ld.relaxed.gpu.global.v2.u32 {%0,%1}, [%2];" : "=r"(v.x), "=r"(v.y) : "l"(p) : "memory");
    return v;
}
__device__ __forceinline__ bool ll_ok(const uint4& v) { return v.x != 0 && v.y != 0 && v.z != 0 && v.w != 0; }
__device__ __forceinline__ void ll_fix16(uint4& v, const void* p) {
    for (int i = 0; !ll_ok(v); i++) { if (i > (1 << 22)) __trap(); v = ld_rlx16(p); }
}
__device__ __forceinline__ void ll_fix8(uint2& v, const void* p) {
    for (int i = 0; v.x == 0 || v.y == 0; i++) { if (i > (1 << 22)) __trap(); v = ld_rlx8(p); }
}
__device__ __forceinline__ void st_rlx4(void* p, uint32_t a) { asm volatile("st.relaxed.gpu.global.u32 [%0], %1;" :: "l"(p), "r"(a) : "memory"); }
__device__ __forceinline__ void st_rlx8(void* p, uint32_t a, uint32_t b) { asm volatile("st.relaxed.gpu.global.v2.u32 [%0], {%1,%2};" :: "l"(p), "r"(a), "r"(b) : "memory"); }
__device__ __forceinline__ void st_rlx16(void* p, uint32_t a, uint32_t b, uint32_t c, uint32_t d) {
    asm volatile("st.relaxed.gpu.global.v4.u32 [%0], {%1,%2,%3,%4};" :: "l"(p), "r"(a), "r"(b), "r"(c), "r"(d) : "memory");
}
__device__ __forceinline__ uint32_t nz(uint32_t w) { return max(w, 1u); }
__device__ __forceinline__ uint32_t nzf(float f) { return max(__float_as_uint(f), 1u); }
__device__ __forceinline__ void mma_bf16(float* d, uint32_t a0, uint32_t a1, uint32_t a2, uint32_t a3, uint32_t b0, uint32_t b1) {
    asm volatile("mma.sync.aligned.m16n8k16.row.col.f32.bf16.bf16.f32 {%0,%1,%2,%3}, {%4,%5,%6,%7}, {%8,%9}, {%0,%1,%2,%3};"
                 : "+f"(d[0]), "+f"(d[1]), "+f"(d[2]), "+f"(d[3]) : "r"(a0), "r"(a1), "r"(a2), "r"(a3), "r"(b0), "r"(b1));
}
__device__ __forceinline__ void ldsm4(uint32_t* r, uint32_t a) {
    asm volatile("ldmatrix.sync.aligned.m8n8.x4.shared.b16 {%0,%1,%2,%3}, [%4];" : "=r"(r[0]), "=r"(r[1]), "=r"(r[2]), "=r"(r[3]) : "r"(a) : "memory");
}
__device__ __forceinline__ void ldsm4t(uint32_t* r, uint32_t a) {
    asm volatile("ldmatrix.sync.aligned.m8n8.x4.trans.shared.b16 {%0,%1,%2,%3}, [%4];" : "=r"(r[0]), "=r"(r[1]), "=r"(r[2]), "=r"(r[3]) : "r"(a) : "memory");
}
__device__ __forceinline__ float bfr(float x) { return __bfloat162float(__float2bfloat16_rn(x)); }
__device__ __forceinline__ uint32_t pk_bf(float lo, float hi) { uint32_t r; asm("cvt.rn.bf16x2.f32 %0, %1, %2;" : "=r"(r) : "f"(hi), "f"(lo)); return r; }
__device__ __forceinline__ uint32_t pk_h(float lo, float hi) { uint32_t r; asm("cvt.rn.f16x2.f32 %0, %1, %2;" : "=r"(r) : "f"(hi), "f"(lo)); return r; }
__device__ __forceinline__ float bf_lo(uint32_t w) { return __uint_as_float(w << 16); }
__device__ __forceinline__ float bf_hi(uint32_t w) { return __uint_as_float(w & 0xFFFF0000u); }
__device__ __forceinline__ uint32_t add_bf2(uint32_t a, uint32_t b) { uint32_t r; asm("add.rn.bf16x2 %0, %1, %2;" : "=r"(r) : "r"(a), "r"(b)); return r; }
__device__ __forceinline__ uint32_t sub_bf2(uint32_t a, uint32_t b) { uint32_t r; asm("sub.rn.bf16x2 %0, %1, %2;" : "=r"(r) : "r"(a), "r"(b)); return r; }
__device__ __forceinline__ float sq_h2(uint32_t w) { float2 f = __half22float2(*(__half2*)&w); return f.x * f.x + f.y * f.y; }
__device__ __forceinline__ float2 ln_stats(float sx, float sxx) {
    float mean = sx * (1.0f / DM);
    float var = fmaxf(sxx * (1.0f / DM) - mean * mean, 0.0f);
    float s = bfr(sqrtf(bfr(bfr(var) + 1e-5f)));
    return make_float2(bfr(mean), 1.0f / s);
}
__device__ __forceinline__ uint32_t ln_apply(uint32_t w, uint32_t m2, float inv) {
    uint32_t d = sub_bf2(w, m2);
    return pk_bf(bf_lo(d) * inv, bf_hi(d) * inv);
}

__device__ __forceinline__ uint32_t ex2_mufu(uint32_t v) { uint32_t r; asm("ex2.approx.f16x2 %0, %1;" : "=r"(r) : "r"(v)); return r; }
__device__ __forceinline__ uint32_t hfma2(uint32_t a, uint32_t b, uint32_t c) { uint32_t r; asm("fma.rn.f16x2 %0, %1, %2, %3;" : "=r"(r) : "r"(a), "r"(b), "r"(c)); return r; }
__device__ __forceinline__ uint32_t ex2_poly(uint32_t w, uint32_t cz, uint32_t ca) {
    uint32_t z;
    asm("lop3.b32 %0, %1, 0x003F003F, %2, 0xEA;" : "=r"(z) : "r"(w), "r"(cz));
    uint32_t g = hfma2(z, ca, 0xD1B5D1B5u);
    uint32_t q = hfma2(g, g, 0xDAB6DAB6u);
    uint32_t h = hfma2(q, q, 0x7BA87BA8u);
    return __funnelshift_l(w, w, 4) + h;
}
constexpr uint32_t POLY_CZ = 0x3C003C00u, POLY_CA = 0x534C534Cu;

struct Params {
    const bf16 *x, *wq, *wk, *wv, *wo, *wr, *wg, *wu, *wd;
    bf16* out;
};

__device__ __noinline__ void attn_safe(const bf16* x, const bf16* wq, int row0, int head, uint32_t* res) {
    const int lane = threadIdx.x & 31, half = lane & 1, row = row0 + (lane >> 1);
    const float2 st = __ldcg(&g_stat1[row]);
    float q[18];
#pragma unroll
    for (int d = 0; d < 18; d++) q[d] = 0.f;
    for (int i = half * 288; i < half * 288 + 288; i++) {
        float xn = bfr(bfr(__bfloat162float(x[row * DM + i]) - st.x) * st.y);
#pragma unroll
        for (int d = 0; d < 18; d++) q[d] += xn * __bfloat162float(wq[i * DM + head * 18 + d]);
    }
#pragma unroll
    for (int d = 0; d < 18; d++) q[d] = bfr(q[d] + __shfl_xor_sync(~0u, q[d], 1)) * 0.23570226039551584f;
    float o[18], l = 0.f, m = -INFINITY;
#pragma unroll
    for (int d = 0; d < 18; d++) o[d] = 0.f;
    for (int pass = 0; pass < 2; pass++) {
        for (int k = half * 1024; k < half * 1024 + 1024; k++) {
            const float4* p = g_kvraw + k * 9;
            float4 e = __ldcg(p + 8);
            float s = q[16] * e.x + q[17] * e.y;
#pragma unroll
            for (int j = 0; j < 4; j++) { float4 a = __ldcg(p + j); s += q[4*j] * a.x + q[4*j+1] * a.y + q[4*j+2] * a.z + q[4*j+3] * a.w; }
            if (pass == 0) { m = fmaxf(m, s); }
            else {
                float pr = __expf(s - m);
                l += pr; o[16] += pr * e.z; o[17] += pr * e.w;
#pragma unroll
                for (int j = 0; j < 4; j++) { float4 a = __ldcg(p + 4 + j); o[4*j] += pr * a.x; o[4*j+1] += pr * a.y; o[4*j+2] += pr * a.z; o[4*j+3] += pr * a.w; }
            }
        }
        if (pass == 0) m = fmaxf(m, __shfl_xor_sync(~0u, m, 1));
    }
    l += __shfl_xor_sync(~0u, l, 1);
    const float inv = 1.0f / l;
    const int g = lane >> 2, t = lane & 3;
#pragma unroll
    for (int p = 0; p < 9; p++) {
        float a = o[2*p] + __shfl_xor_sync(~0u, o[2*p], 1), b = o[2*p+1] + __shfl_xor_sync(~0u, o[2*p+1], 1);
        uint32_t w = pk_bf(a * inv, b * inv);
        uint32_t v0 = __shfl_sync(~0u, w, 2 * g), v1 = __shfl_sync(~0u, w, 2 * g + 16);
        if (p == t) { res[2] = v0; res[3] = v1; }
        if (p == t + 4) { res[4] = v0; res[5] = v1; }
        if (p == 8) { res[0] = v0; res[1] = v1; }
    }
}

__global__ void __launch_bounds__(NTHR, 1)
fused_block(const __grid_constant__ CUtensorMap tm_x, const __grid_constant__ CUtensorMap tm_wq,
            const __grid_constant__ CUtensorMap tm_wqt, const __grid_constant__ CUtensorMap tm_g,
            const __grid_constant__ CUtensorMap tm_u, const Params P) {
    extern __shared__ __align__(1024) uint8_t smem[];
    const uint32_t sb = (uint32_t)__cvta_generic_to_shared(smem);
    const int tid = threadIdx.x, lane = tid & 31;
    const int warp = __shfl_sync(~0u, tid >> 5, 0);
    const int cta = blockIdx.x, qb = cta >> 2, hg = cta & 3;
    const int g = lane >> 2, t = lane & 3;
    uint8_t* const misc = smem + SM_MISC;
    const uint32_t bars = sb + SM_BAR;
#define BAR(i) (bars + 8 * (i))

    const int wg = warp >> 2, wq4 = warp & 3;
    if (wg == 0) {
        if (warp == 0) TS(0);
        if (tid < B_NUM) {
            if (sb & 1023) __trap();
            const int cnt = tid < B_KVF ? 4 : (tid < B_KVD ? 1 : (tid < B_AUX || tid == B_QRD ? 16 :
                            (tid == B_WO0 ? 7 : (tid == B_OHI ? 32 : (tid >= B_OC && tid <= B_OE ? 4 : (tid == B_GU ? 2 : 1))))));
            mbar_init(BAR(tid), cnt);
            asm volatile("fence.mbarrier_init.release.cluster;" ::: "memory");
        }
        BAR_SYNC(9, 128);
        const CUtensorMap* const mytm = warp == 0 ? &tm_x : (warp == 3 ? &tm_wqt : &tm_wq);
        const uint32_t mybytes = warp == 3 ? 2048 : 8192;
        if (lane == 0) {
            for (int c = 0; c < (warp == 0 ? 9 : 8); c++) {
                mbar_expect(BAR(B_FULL + c), mybytes);
                if (warp == 0) tma2d(sb + SM_X + c * 8192, mytm, c * 64, qb * 64, BAR(B_FULL + c));
                else tma2d(sb + (c == 0 ? SM_WQ0 : (c - 1) * 18432) + (warp - 1) * 8192, mytm, hg * 144 + (warp - 1) * 64, c * 64, BAR(B_FULL + c));
            }
        }
        __syncwarp();
        BAR_ARRIVE(1, NTHR);
        if (cta < 72) {
            uint4 v[5];
#pragma unroll
            for (int j = 0; j < 5; j++) {
                const int k = tid + 128 * j;
                v[j] = (j < 4 || tid < 64) ? __ldg((const uint4*)(P.wq + k * DM + cta * 8)) : make_uint4(0, 0, 0, 0);
            }
            float s[8];
#pragma unroll
            for (int i = 0; i < 8; i++) s[i] = 0.f;
#pragma unroll
            for (int j = 0; j < 5; j++) {
                s[0] += bf_lo(v[j].x); s[1] += bf_hi(v[j].x); s[2] += bf_lo(v[j].y); s[3] += bf_hi(v[j].y);
                s[4] += bf_lo(v[j].z); s[5] += bf_hi(v[j].z); s[6] += bf_lo(v[j].w); s[7] += bf_hi(v[j].w);
            }
            const bool u4 = lane & 16, u2 = lane & 8, u1 = lane & 4;
#pragma unroll
            for (int i = 0; i < 4; i++) s[i] = (u4 ? s[i + 4] : s[i]) + __shfl_xor_sync(~0u, u4 ? s[i] : s[i + 4], 16);
#pragma unroll
            for (int i = 0; i < 2; i++) s[i] = (u2 ? s[i + 2] : s[i]) + __shfl_xor_sync(~0u, u2 ? s[i] : s[i + 2], 8);
            s[0] = (u1 ? s[1] : s[0]) + __shfl_xor_sync(~0u, u1 ? s[0] : s[1], 4);
            s[0] += __shfl_xor_sync(~0u, s[0], 2);
            s[0] += __shfl_xor_sync(~0u, s[0], 1);
            if (t == 0) g_colsum[warp][cta * 8 + g] = s[0];
            __syncwarp();
            if (lane == 0) red_release(&g_cnt[0]);
        }
        float acc[72];
#pragma unroll
        for (int c = 0; c < 9; c++) {
            const uint32_t slot = sb + ((c == 0 || c == 8) ? SM_WQ0 : (c - 1) * 18432);
            if (c == 2 && warp != 0 && lane == 0) {
                mbar_wait(BAR(B_QC + 0));
                mbar_expect(BAR(B_FULL + 8), mybytes);
                tma2d(sb + SM_WQ0 + (warp - 1) * 8192, mytm, hg * 144 + (warp - 1) * 64, 512, BAR(B_FULL + 8));
            }
            mbar_wait(BAR(B_FULL + c));
            if (c == 0) TS(8);
            WG_FENCE();
#pragma unroll
            for (int s = 0; s < 4; s++) {
                const uint64_t da = mkdesc(sb + SM_X + c * 8192 + s * 32, 16, 1024, 1);
                const uint64_t db = mkdesc(slot + s * 2048, 8192, 1024, 1);
                const uint64_t dt = mkdesc(slot + 16384 + s * 512, 256, 256, 3);
                if (c == 0 && s == 0) { wgz_ss_n128_f32_bf16(acc, da, db); wgz_ss_n16_f32_bf16(acc + 64, da, dt); }
                else { wg_ss_n128_f32_bf16(acc, da, db); wg_ss_n16_f32_bf16(acc + 64, da, dt); }
            }
            WG_COMMIT();
            if (c > 0) { WG_WAIT(1); if (lane == 0) mbar_arrive(BAR(B_QC + c - 1)); }
        }
        WG_WAIT(0);
        if (lane == 0) mbar_arrive(BAR(B_QC + 8));
#pragma unroll
        for (int i = 0; i < 72; i++) asm volatile("" : "+f"(acc[i]) :: "memory");
        TS(9);
        mbar_wait(BAR(B_QC + 8));
        mbar_wait(BAR(B_AUX));
        TS(10);
        const float kq = 0.23570226039551584f * 1.4426950408889634f / 512.0f;
        const float2 s0 = ((const float2*)(misc + MI_STAT))[wq4 * 16 + g], s1 = ((const float2*)(misc + MI_STAT))[wq4 * 16 + g + 8];
        const float a0 = s0.y * kq, a1 = s1.y * kq, b0 = -s0.x * a0, b1 = -s1.x * a1;
        uint8_t* qs = smem + SM_A + (wq4 * 16 + g) * 304 + t * 4;
#pragma unroll
        for (int b = 0; b < 18; b++) {
            const float2 cs = ((const float2*)(misc + MI_CS))[4 * b + t];
            *(uint32_t*)(qs + b * 16) = pk_h(fmaf(acc[4*b], a0, cs.x * b0), fmaf(acc[4*b+1], a0, cs.y * b0));
            *(uint32_t*)(qs + 8 * 304 + b * 16) = pk_h(fmaf(acc[4*b+2], a1, cs.x * b1), fmaf(acc[4*b+3], a1, cs.y * b1));
        }
    } else {
        const int wi = warp - 4, kp = wi / 3, set = wi % 3, R0 = cta * 16;
        float* const pp = (float*)misc;
        {
            const int kb = 144 * kp + 36 * t;
            uint2 xa[9], xb[9];
            uint32_t w[36];
            const bf16* wsrc = set == 0 ? P.wk + 2 * g : (set == 1 ? P.wv + 2 * g : (g == 0 ? P.wk + 16 : P.wv + 16));
#pragma unroll
            for (int s = 0; s < 9; s++) {
                xa[s] = __ldg((const uint2*)(P.x + (R0 + g) * DM + kb + 4 * s));
                xb[s] = __ldg((const uint2*)(P.x + (R0 + g + 8) * DM + kb + 4 * s));
            }
#pragma unroll
            for (int i = 0; i < 36; i++) w[i] = (set < 2 || g < 2) ? __ldg((const uint32_t*)(wsrc + (kb + i) * 18)) : 0x3F803F80u;
            float ae[4] = {0, 0, 0, 0}, ao[4] = {0, 0, 0, 0}, ce[4] = {0, 0, 0, 0}, co[4] = {0, 0, 0, 0}, g1[4] = {0, 0, 0, 0}, g2[4] = {0, 0, 0, 0};
            const uint32_t one = 0x3F803F80u;
#pragma unroll
            for (int s = 0; s < 9; s++) {
                const uint32_t e0 = __byte_perm(w[4*s], w[4*s+1], 0x5410), e1 = __byte_perm(w[4*s+2], w[4*s+3], 0x5410);
                const uint32_t o0 = __byte_perm(w[4*s], w[4*s+1], 0x7632), o1 = __byte_perm(w[4*s+2], w[4*s+3], 0x7632);
                mma_bf16(ae, xa[s].x, xb[s].x, xa[s].y, xb[s].y, e0, e1);
                mma_bf16(ao, xa[s].x, xb[s].x, xa[s].y, xb[s].y, o0, o1);
                mma_bf16(ce, one, one, one, one, e0, e1);
                mma_bf16(co, one, one, one, one, o0, o1);
                if (set == 2) {
                    mma_bf16(g1, xa[s].x, xb[s].x, xa[s].y, xb[s].y, xa[s].x, xa[s].y);
                    mma_bf16(g2, xa[s].x, xb[s].x, xa[s].y, xb[s].y, xb[s].x, xb[s].y);
                }
            }
            float* pk = pp + kp * 680;
            if (set < 2 || t == 0) {
                const int col = set * 16 + 4 * t;
                *(float4*)(pk + g * 40 + col) = make_float4(ae[0], ao[0], ae[1], ao[1]);
                *(float4*)(pk + (g + 8) * 40 + col) = make_float4(ae[2], ao[2], ae[3], ao[3]);
                if (g == 0) *(float4*)(pk + 640 + col) = make_float4(ce[0], co[0], ce[1], co[1]);
            }
            if (set == 2) {
                if (t == 1) { pk[g * 40 + 36] = ae[0]; pk[(g + 8) * 40 + 36] = ae[2]; }
                if (t == (g >> 1)) { pk[g * 40 + 38] = (g & 1) ? g1[1] : g1[0]; pk[(g + 8) * 40 + 38] = (g & 1) ? g2[3] : g2[2]; }
            }
        }
        if (wi == 0) TS(12);
        BAR_SYNC(1, NTHR);
        if (wi < 8) {
            const int r = 2 * wi + (lane >> 4), l = lane & 15, lc = min(l, 8);
            float4 a = make_float4(0, 0, 0, 0), cs = a;
            float sx = 0.f, sxx = 0.f;
#pragma unroll
            for (int k = 0; k < 4; k++) {
                const float4 u = *(const float4*)(pp + k * 680 + r * 40 + 4 * lc), v = *(const float4*)(pp + k * 680 + 640 + 4 * lc);
                a.x += u.x; a.y += u.y; a.z += u.z; a.w += u.w; cs.x += v.x; cs.y += v.y; cs.z += v.z; cs.w += v.w;
                sx += pp[k * 680 + r * 40 + 36]; sxx += pp[k * 680 + r * 40 + 38];
            }
            const float2 st = ln_stats(sx, sxx);
            a.x = bfr((a.x - st.x * cs.x) * st.y); a.y = bfr((a.y - st.x * cs.y) * st.y);
            a.z = bfr((a.z - st.x * cs.z) * st.y); a.w = bfr((a.w - st.x * cs.w) * st.y);
            float n2 = (l < 4 || l == 8) ? a.x * a.x + a.y * a.y : 0.f;
            if (l < 4) n2 += a.z * a.z + a.w * a.w;
            uint32_t vm = l >= 4 ? max(__float_as_uint(fabsf(a.z)), __float_as_uint(fabsf(a.w))) : 0u;
            if (l >= 4 && l < 8) vm = max(vm, max(__float_as_uint(fabsf(a.x)), __float_as_uint(fabsf(a.y))));
#pragma unroll
            for (int d = 1; d < 16; d <<= 1) { n2 += __shfl_xor_sync(~0u, n2, d); vm = max(vm, __shfl_xor_sync(~0u, vm, d)); }
            if (l < 9) g_kvraw[(R0 + r) * 9 + l] = a;
            if (l == 0) { pp[r * 40 + 39] = n2; pp[r * 40 + 37] = __uint_as_float(vm); }
            BAR_SYNC(3, 256);
            const uint32_t mine = __float_as_uint(n2), other = __float_as_uint(pp[l * 40 + 39]);
            const uint32_t bal = __ballot_sync(~0u, other > mine || (other == mine && l < r));
            const int rank = __popc((bal >> (lane & 16)) & 0xFFFFu);
            const int pj = rank >> 1, blk = pj == 0 ? 0 : (pj == 1 ? 4 : (pj < 5 ? pj - 1 : pj));
            const bool mu = rank < 4;
            const float ks = mu ? 512.f : (1.f / 512.f), vs = mu ? 128.f : -1.f;
            uint8_t* stg = misc + 5440 + blk * 160 + (rank & 1) * 16;
            if (l < 8) {
                const float sc = l < 4 ? ks : vs;
                *(uint2*)(stg + (l < 4 ? (l >> 1) : 3 + ((l - 4) >> 1)) * 32 + (l & 1) * 8) = make_uint2(pk_h(a.x * sc, a.y * sc), pk_h(a.z * sc, a.w * sc));
            } else if (l == 8) {
                *(uint4*)(stg + 64) = make_uint4(pk_h(a.x * ks, a.y * ks), pk_h(mu ? -3072.f : (17.f / 512.f), vs), 0u, pk_h(a.z * vs, a.w * vs));
            } else if (l == 9) {
                ((float2*)(misc + 6720))[r] = st;
                if (rank == 0) *(float*)(misc + 6852) = n2;
                if (rank == 4) *(float*)(misc + 6848) = n2;
            }
            BAR_SYNC(4, 256);
            if (wi == 0) {
#pragma unroll
                for (int it = 0; it < 3; it++) {
                    const int i = lane + 32 * it;
                    if (i < 80) g_kv[(qb * 8 + i / 10) * 40 + ((i % 10) >> 1) * 8 + 2 * hg + (i & 1)] = ((const uint4*)(misc + 5440))[i];
                }
                if (lane < 8) ((float4*)(g_stat1 + R0))[lane] = ((const float4*)(misc + 6720))[lane];
                const uint32_t vmx = __reduce_max_sync(~0u, __float_as_uint(pp[l * 40 + 37]));
                if (lane == 0) g_info[cta] = make_float4(*(float*)(misc + 6848), *(float*)(misc + 6852), __uint_as_float(vmx), 0.f);
                __syncwarp();
                if (lane == 0) red_release(&g_cnt[0]);
                TS(13);
            }
        } else if (wi == 8) {
            if (lane == 0) {
                poll_counter(&g_cnt[0], CNT1);
                PROXY_FENCE();
                for (int j = 0; j < 2; j++) {
                    mbar_wait(BAR(B_QC + j + 2));
                    mbar_expect(BAR(B_KVF + j), 20480);
                    bulk_ld(sb + j * 20480, g_kv + j * 1280, 20480, BAR(B_KVF + j));
                }
            }
            __syncwarp();
            TS(1);
            float4 st = __ldcg((const float4*)(g_stat1 + qb * 64) + lane);
            float4 c0[4], c1[4], inf[4];
#pragma unroll
            for (int j = 0; j < 4; j++) {
                c0[j] = __ldcg((const float4*)(g_colsum[j] + hg * 144) + lane);
                if (lane < 4) c1[j] = __ldcg((const float4*)(g_colsum[j] + hg * 144) + 32 + lane);
                inf[j] = __ldcg(g_info + 4 * lane + j);
            }
            for (int i = lane; i < (10880 - MI_NC) / 16; i += 32) ((uint4*)(misc + MI_NC))[i] = make_uint4(0, 0, 0, 0);
            ((float4*)(misc + MI_STAT))[lane] = st;
            ((float4*)(misc + MI_CS))[lane] = make_float4((c0[0].x + c0[1].x) + (c0[2].x + c0[3].x), (c0[0].y + c0[1].y) + (c0[2].y + c0[3].y),
                                                         (c0[0].z + c0[1].z) + (c0[2].z + c0[3].z), (c0[0].w + c0[1].w) + (c0[2].w + c0[3].w));
            if (lane < 4)
                ((float4*)(misc + MI_CS))[32 + lane] = make_float4((c1[0].x + c1[1].x) + (c1[2].x + c1[3].x), (c1[0].y + c1[1].y) + (c1[2].y + c1[3].y),
                                                                  (c1[0].z + c1[1].z) + (c1[2].z + c1[3].z), (c1[0].w + c1[1].w) + (c1[2].w + c1[3].w));
            uint32_t kp2 = 0, ka = 0, vm = 0;
#pragma unroll
            for (int j = 0; j < 4; j++) {
                kp2 = max(kp2, __float_as_uint(inf[j].x)); ka = max(ka, __float_as_uint(inf[j].y)); vm = max(vm, __float_as_uint(inf[j].z));
            }
            kp2 = max(kp2, __shfl_xor_sync(~0u, kp2, 1)); kp2 = max(kp2, __shfl_xor_sync(~0u, kp2, 2));
            ka = __reduce_max_sync(~0u, ka); vm = __reduce_max_sync(~0u, vm);
            uint32_t* kpp = (uint32_t*)(misc + MI_KP);
            if (t == 0) kpp[g] = kp2;
            if (lane == 0) { kpp[8] = ka; kpp[9] = vm; kpp[10] = 0; }
            PROXY_FENCE_SMEM();
            __syncwarp();
            if (lane == 0) {
                mbar_arrive(BAR(B_AUX));
                for (int j = 2; j < 8; j++) {
                    mbar_wait(BAR(B_QC + min(j + 2, 8)));
                    mbar_expect(BAR(B_KVF + j), 20480);
                    bulk_ld(sb + j * 20480, g_kv + j * 1280, 20480, BAR(B_KVF + j));
                }
            }
            __syncwarp();
            TS(2);
        } else {
            uint4 v[4];
#pragma unroll
            for (int it = 0; it < 4; it++) {
                const int l = tid - 416 + 96 * it;
                if (l < 324) {
                    const int i = cta * 324 + l, h2 = i / 10368, rem = i % 10368, ci = rem / 144, c = (rem % 144) >> 3, j = rem & 7;
                    const int r = ci / 36, cc = ci % 36;
                    const int k = 144 * ((h2 + cc / 9) & 3) + 72 * r + 8 * (cc % 9) + j;
                    v[it] = __ldg((const uint4*)(P.wo + k * DM + h2 * 144 + c * 8));
                }
            }
#pragma unroll
            for (int it = 0; it < 4; it++) { const int l = tid - 416 + 96 * it; if (l < 324) g_wo[cta * 324 + l] = v[it]; }
        }
    }
    BAR_SYNC(5, 512);
    if (warp == 0) TS(11);
    if (warp == 4) {
        constexpr int ZB = sizeof(LLScratch) / NCTA;
        if (lane < 7) {
            const int off = lane * 8192, n = min(8192, ZB - off);
            asm volatile("cp.async.bulk.global.shared::cta.bulk_group [%0], [%1], %2;"
                         :: "l"((uint8_t*)&g_ll + cta * ZB + off), "r"(sb + SM_MISC + MI_RED), "r"(n) : "memory");
            asm volatile("cp.async.bulk.commit_group;" ::: "memory");
        }
        __syncwarp();
    }
    int wo_next = -1;

    uint32_t ow[6];
    const int orow = wq4 * 16 + g;
    const int ok0 = 18 * wg + 2 * t;
    const uint32_t oa1 = (ok0 >> 3) * 1024 + orow * 16 + (ok0 & 7) * 2;
    const uint32_t oa0 = ((18 * wg + 16) >> 3) * 1024 + orow * 16 + ((18 * wg + 16) & 7) * 2;
#pragma unroll 1
    for (int rnd = 0; rnd < 2; rnd++) {
        uint32_t q[8];
        {
            const uint8_t* qs = smem + SM_A + orow * 304 + (4 * rnd + wg) * 36;
            q[0] = *(const uint32_t*)(qs + 4 * t); q[1] = *(const uint32_t*)(qs + 8 * 304 + 4 * t);
            q[2] = *(const uint32_t*)(qs + 16 + 4 * t); q[3] = *(const uint32_t*)(qs + 8 * 304 + 16 + 4 * t);
            q[4] = *(const uint32_t*)(qs + 32); q[5] = *(const uint32_t*)(qs + 8 * 304 + 32);
            q[6] = *(volatile uint32_t*)(misc + MI_KP + 40); q[7] = *(volatile uint32_t*)(misc + MI_KP + 40);
        }
        if (t != 0) { q[4] = 0; q[5] = 0; }
        float n0 = sq_h2(q[0]) + sq_h2(q[2]) + sq_h2(q[4]), n1 = sq_h2(q[1]) + sq_h2(q[3]) + sq_h2(q[5]);
        if (t == 1) { q[4] = 0x1800u; q[5] = 0x1800u; }
        if (rnd == 1) { __syncwarp(); if (lane == 0) mbar_arrive(BAR(B_QRD)); }
        n0 += __shfl_xor_sync(~0u, n0, 1); n1 += __shfl_xor_sync(~0u, n1, 1);
        n0 += __shfl_xor_sync(~0u, n0, 2); n1 += __shfl_xor_sync(~0u, n1, 2);
        const float qn = __uint_as_float(__reduce_max_sync(~0u, max(__float_as_uint(n0), __float_as_uint(n1)))) * 262144.0f;
        const float* kpp = (const float*)(misc + MI_KP);
        uint32_t chk = __ballot_sync(~0u, !(qn * kpp[lane & 7] <= 222.0f));
        const float ka = kpp[8], vmx = kpp[9];
        bool bad = !(qn * ka <= 4096.0f && qn <= 4096.0f && ka <= 4096.0f && vmx <= 500.0f && vmx >= 0.015625f);
        uint32_t cz = POLY_CZ + q[6], ca = POLY_CA + q[6], accor = 0;
        chk = (chk & 0xFF) | (rnd == 0 ? (warp == 4 ? 0x0600u : (warp == 8 ? 0x4000u : 0u)) : (warp == 12 ? 0xFF00u : 0x7F00u));

        float o[12];
#pragma unroll
        for (int i = 0; i < 12; i++) { o[i] = 0.f; asm volatile("" : "+f"(o[i]) :: "memory"); }
        uint64_t dk = mkdesc(sb, 128, 640, 0), dv = mkdesc(sb + 256, 640, 128, 0);
#pragma unroll 1
        for (int j = 0; j < 8; j++) {
            uint32_t s[64];
            if (rnd == 0) mbar_wait(BAR(B_KVF + j));
            WG_FENCE();
            wgz_rs_n256_f16_f16(s, q[0], q[1], q[2], q[3], dk);
            wg_rs_n256_f16_f16(s, q[4], q[5], q[6], q[7], dk + 16);
            WG_COMMIT();
            WG_WAIT(0);
#pragma unroll
            for (int i = 0; i < 64; i++) asm volatile("" : "+r"(s[i]) :: "memory");
            if (chk & 1) {
#pragma unroll
                for (int i = 0; i < 64; i += 2) if ((i >> 1) & 3) accor |= s[i] | s[i + 1];
            }
#pragma unroll
            for (int i = 0; i < 64; i++) s[i] = ((i >> 1) & 3) ? ex2_poly(s[i], cz, ca) : ex2_mufu(s[i]);
#pragma unroll
            for (int i = 0; i < 64; i++) asm volatile("" : "+r"(s[i]) :: "memory");
            WG_FENCE();
#pragma unroll
            for (int c = 0; c < 16; c++) wg_rs_n24_f32_f16(o, s[4*c], s[4*c+1], s[4*c+2], s[4*c+3], dv + c * 80);
            WG_COMMIT();
            WG_WAIT(0);
            if (chk & 0x100) {
                if (rnd == 0) {
                    if (warp == 8) {
                        if (lane == 0) { poll_counter(&g_cnt[32], CNT2); mbar_arrive(BAR(B_ZOK)); }
                    } else if (j == 1) {
                        if (lane < 12) {
                            const bf16* w = lane < 4 ? P.wg : (lane < 8 ? P.wu : P.wd);
                            l2_prefetch(w + cta * 20736 + (lane & 3) * 5184, 10368);
                        }
                    } else {
                        asm volatile("cp.async.bulk.wait_group 0;" ::: "memory");
                        PROXY_FENCE();
                        __syncwarp();
                        if (lane == 0) red_release(&g_cnt[32]);
                    }
                } else {
                    if (j < 6 && lane == 0) mbar_arrive(BAR(B_KVD + j));
                    if (warp == 12 && lane == 0) {
                        if (j == 0) PROXY_FENCE();
                        if (j == 3) {
                            mbar_expect(BAR(B_OHT), 3 * 9216);
                            for (int u = 1; u < 4; u++) bulk_ld(sb + SM_OHI + u * 9216, g_ll.o[qb][(hg + u) & 3], 9216, BAR(B_OHT));
                        }
                        while (wo_next < 6) {
                            const uint32_t wb = wo_next < 0 ? BAR(B_QRD) : BAR(B_KVD + wo_next);
                            if (j == 7) mbar_wait(wb); else if (wo_next >= j || !mbar_test(wb)) break;
                            const int s0 = wo_next < 0 ? 26 : wo_next * 40 / 9, s1 = wo_next < 0 ? 30 : (wo_next + 1) * 40 / 9;
                            mbar_expect(BAR(B_WO0), (s1 - s0) * 4608);
                            bulk_ld(sb + (wo_next < 0 ? SM_A : s0 * 4608), g_wo + hg * 10368 + s0 * 288, (s1 - s0) * 4608, BAR(B_WO0));
                            wo_next++;
                        }
                    }
                    if (j == 6) {
                        mbar_wait(BAR(B_OHT));
                        for (int i = 576 + tid; i < 2304; i += 512) {
                            uint4* p = (uint4*)(smem + SM_OHI) + i;
                            uint4 v = *p;
                            if (!ll_ok(v)) { ll_fix16(v, (const uint4*)g_ll.o[qb][(hg + i / 576) & 3] + i % 576); *p = v; }
                        }
                        PROXY_FENCE_SMEM();
                        __syncwarp();
                        if (lane == 0) mbar_arrive(BAR(B_OHI));
                    }
                }
                __syncwarp();
            }
            chk >>= 1;
            dk += 1280; dv += 1280;
        }
#pragma unroll
        for (int i = 0; i < 12; i++) asm volatile("" : "+f"(o[i]) :: "memory");
        if (wq4 == 0) TS(14 + 4 * rnd + wg);
        const float l0 = __shfl_sync(~0u, o[1], (lane & 28) | 1), l1 = __shfl_sync(~0u, o[3], (lane & 28) | 1);
        bad = bad || (accor & 0xF800F800u) || !(l0 >= 64.0f && l0 <= 1e30f && l1 >= 64.0f && l1 <= 1e30f);
        const float i0 = 1.0f / l0, i1 = 1.0f / l1;
        ow[0] = pk_bf(o[0] * i0, o[1] * i0); ow[1] = pk_bf(o[2] * i1, o[3] * i1);
        ow[2] = pk_bf(o[4] * i0, o[5] * i0); ow[3] = pk_bf(o[6] * i1, o[7] * i1);
        ow[4] = pk_bf(o[8] * i0, o[9] * i0); ow[5] = pk_bf(o[10] * i1, o[11] * i1);
        if (__any_sync(~0u, bad)) {
            uint32_t res[6];
            attn_safe(P.x, P.wq, qb * 64 + wq4 * 16, hg * 8 + 4 * rnd + wg, res);
#pragma unroll
            for (int i = 0; i < 6; i++) ow[i] = res[i];
        }
#pragma unroll
        for (int i = 0; i < 6; i++) ow[i] = nz(ow[i]);
        mbar_wait(BAR(B_ZOK));
        uint8_t* go = (uint8_t*)g_ll.o[qb][4 * rnd + hg];
        st_rlx4(go + oa1, ow[2]); st_rlx4(go + oa1 + 128, ow[3]);
        st_rlx4(go + oa1 + 1024, ow[4]); st_rlx4(go + oa1 + 1152, ow[5]);
        if (t == 3) { st_rlx4(go + oa0, ow[0]); st_rlx4(go + oa0 + 128, ow[1]); }
        if (rnd == 0) {
            uint8_t* so = smem + SM_OHI;
            *(uint32_t*)(so + oa1) = ow[2]; *(uint32_t*)(so + oa1 + 128) = ow[3];
            *(uint32_t*)(so + oa1 + 1024) = ow[4]; *(uint32_t*)(so + oa1 + 1152) = ow[5];
            if (t == 3) { *(uint32_t*)(so + oa0) = ow[0]; *(uint32_t*)(so + oa0 + 128) = ow[1]; }
            PROXY_FENCE_SMEM();
            __syncwarp();
            if (lane == 0) mbar_arrive(BAR(B_OHI));
        }
    }

    uint32_t hw[36];
    float2 st0, st1;
    uint32_t key0 = 0, key1 = 0;
    if (wg == 0) {
        float acc[72];
        mbar_wait(BAR(B_WO0));
        mbar_wait(BAR(B_OHI));
        WG_FENCE();
#pragma unroll
        for (int s = 0; s < 18; s++) {
            const uint64_t da = mkdesc(sb + SM_OHI + s * 2048, 1024, 128, 0), db = mkdesc(sb + s * 4608, 2304, 128, 0);
            if (s == 0) wgz_ss_n144_f32_bf16(acc, da, db); else wg_ss_n144_f32_bf16(acc, da, db);
            if (s == 10) WG_COMMIT();
        }
        WG_COMMIT();
        BAR_SYNC(6, 512);
        {
            uint8_t* so = smem + SM_OLO;
            *(uint32_t*)(so + oa1) = ow[2]; *(uint32_t*)(so + oa1 + 128) = ow[3];
            *(uint32_t*)(so + oa1 + 1024) = ow[4]; *(uint32_t*)(so + oa1 + 1152) = ow[5];
            if (t == 3) { *(uint32_t*)(so + oa0) = ow[0]; *(uint32_t*)(so + oa0 + 128) = ow[1]; }
            PROXY_FENCE_SMEM();
        }
        WG_WAIT(1);
        if (lane == 0) mbar_arrive(BAR(B_OC));
        BAR_SYNC(7, 512);
        TS(22);
        WG_FENCE();
#pragma unroll
        for (int s = 18; s < 30; s++) {
            const uint64_t da = mkdesc(sb + SM_OLO + (s - 18) * 2048, 1024, 128, 0);
            const uint64_t db = mkdesc(sb + (s < 26 ? s * 4608 : SM_A + (s - 26) * 4608), 2304, 128, 0);
            wg_ss_n144_f32_bf16(acc, da, db);
        }
        WG_COMMIT();
        WG_WAIT(1);
        if (lane == 0) mbar_arrive(BAR(B_OM));
        mbar_wait(BAR(B_WO1));
        WG_FENCE();
#pragma unroll
        for (int s = 30; s < 36; s++) {
            const uint64_t da = mkdesc(sb + SM_OLO + (s - 18) * 2048, 1024, 128, 0), db = mkdesc(sb + (s - 30) * 4608, 2304, 128, 0);
            wg_ss_n144_f32_bf16(acc, da, db);
        }
        WG_COMMIT();
        uint32_t wb[18];
#pragma unroll
        for (int b = 0; b < 18; b++) wb[b] = g == 1 ? __ldg((const uint32_t*)(P.wr + hg * 144 + 8 * b + 2 * t)) : 0x3F803F80u;
        WG_WAIT(0);
        if (lane == 0) mbar_arrive(BAR(B_OE));
#pragma unroll
        for (int i = 0; i < 72; i++) asm volatile("" : "+f"(acc[i]) :: "memory");
        TS(23);
        float sm[4] = {0, 0, 0, 0}, g1[4] = {0, 0, 0, 0}, g2[4] = {0, 0, 0, 0}, sw[4] = {0, 0, 0, 0};
        const uint32_t xaddr = sb + SM_XS + (wq4 * 16 + (lane & 15)) * 304 + (lane >> 4) * 16;
#pragma unroll
        for (int s = 0; s < 9; s++) {
            uint32_t xr[4];
            ldsm4(xr, xaddr + s * 32);
#pragma unroll
            for (int i = 0; i < 4; i++) hw[4*s+i] = nz(add_bf2(xr[i], pk_bf(acc[8*s+2*i], acc[8*s+2*i+1])));
            mma_bf16(sm, hw[4*s], hw[4*s+1], hw[4*s+2], hw[4*s+3], wb[2*s], wb[2*s+1]);
            mma_bf16(g1, hw[4*s], hw[4*s+1], hw[4*s+2], hw[4*s+3], hw[4*s], hw[4*s+2]);
            mma_bf16(g2, hw[4*s], hw[4*s+1], hw[4*s+2], hw[4*s+3], hw[4*s+1], hw[4*s+3]);
            mma_bf16(sw, 0x3F803F80u, 0x3F803F80u, 0x3F803F80u, 0x3F803F80u, wb[2*s], wb[2*s+1]);
        }
        const int dl = (lane & 28) | (g >> 1);
        const float q0 = __shfl_sync(~0u, (g & 1) ? g1[1] : g1[0], dl), q1 = __shfl_sync(~0u, (g & 1) ? g2[3] : g2[2], dl);
        float4* part = g_ll.part[qb][hg] + orow;
        if (t == 0) {
            st_rlx16(part, nzf(sm[0]), nzf(q0), nzf(sm[1]), nzf(sw[1]));
            st_rlx16(part + 8, nzf(sm[2]), nzf(q1), nzf(sm[3]), nzf(sw[1]));
        }
        uint32_t* gh = g_ll.h[qb * 64 + orow] + hg * 72 + t;
#pragma unroll
        for (int b = 0; b < 18; b++) { st_rlx4(gh + 4 * b, hw[2*b]); st_rlx4(gh + 8 * 288 + 4 * b, hw[2*b+1]); }
        const float4* pin = g_ll.part[qb][t] + orow;
        uint4 p0 = ld_rlx16(pin), p1 = ld_rlx16(pin + 8);
        ll_fix16(p0, pin); ll_fix16(p1, pin + 8);
        float v[8] = {__uint_as_float(p0.x), __uint_as_float(p0.y), __uint_as_float(p0.z), __uint_as_float(p0.w),
                      __uint_as_float(p1.x), __uint_as_float(p1.y), __uint_as_float(p1.z), 0.f};
        __syncwarp();
#pragma unroll
        for (int i = 0; i < 7; i++) { v[i] += __shfl_xor_sync(~0u, v[i], 1); v[i] += __shfl_xor_sync(~0u, v[i], 2); }
        st0 = ln_stats(v[0], v[1]); st1 = ln_stats(v[4], v[5]);
        uint32_t u0 = __float_as_uint((v[2] - st0.x * v[3]) * st0.y), u1 = __float_as_uint((v[6] - st1.x * v[3]) * st1.y);
        u0 = (u0 & 0x80000000u) ? ~u0 : (u0 | 0x80000000u); u1 = (u1 & 0x80000000u) ? ~u1 : (u1 | 0x80000000u);
        const int row = qb * 64 + orow;
        key0 = nz((u0 & 0xFFFFF800u) | (2047 - row)); key1 = nz((u1 & 0xFFFFF800u) | (2047 - (row + 8)));
        if (wq4 == hg) {
            if (t == 0) { st_rlx4(&g_ll.rkey[row], key0); st_rlx8(&g_ll.stat2[row], nzf(st0.x), nzf(st0.y)); }
            if (t == 1) { st_rlx4(&g_ll.rkey[row + 8], key1); st_rlx8(&g_ll.stat2[row + 8], nzf(st1.x), nzf(st1.y)); }
        }
        TS(24);
    } else {
        const uint4* src = (const uint4*)g_ll.o[qb][4 + ((hg + wg) & 3)] + (tid & 127);
        uint4 v[5];
#pragma unroll
        for (int j = 0; j < 5; j++) if (j < 4 || (tid & 127) < 64) v[j] = ld_rlx16(src + j * 128);
        BAR_SYNC(6, 512);
        uint8_t* so = smem + SM_OLO;
        *(uint32_t*)(so + oa1) = ow[2]; *(uint32_t*)(so + oa1 + 128) = ow[3];
        *(uint32_t*)(so + oa1 + 1024) = ow[4]; *(uint32_t*)(so + oa1 + 1152) = ow[5];
        if (t == 3) { *(uint32_t*)(so + oa0) = ow[0]; *(uint32_t*)(so + oa0 + 128) = ow[1]; }
        uint4* dst = (uint4*)(so + wg * 9216) + (tid & 127);
#pragma unroll
        for (int j = 0; j < 5; j++) if (j < 4 || (tid & 127) < 64) { ll_fix16(v[j], src + j * 128); dst[j * 128] = v[j]; }
        PROXY_FENCE_SMEM();
        BAR_ARRIVE(7, 512);
        if (warp == 12) {
            if (lane == 0) {
                mbar_wait(BAR(B_OC));
                mbar_expect(BAR(B_WO1), 6 * 4608 + 64 * 288);
                bulk_ld(sb, g_wo + hg * 10368 + 30 * 288, 6 * 4608, BAR(B_WO1));
            }
            __syncwarp();
            for (int r = lane; r < 64; r += 32) bulk_ld(sb + SM_XS + r * 304, P.x + (qb * 64 + r) * DM + hg * 144, 288, BAR(B_WO1));
        } else if (warp == 13) {
            const int fc0 = (cta * 36) & ~7;
            if (lane == 0) {
                mbar_wait(BAR(B_OM));
                mbar_expect(BAR(B_GU), 4 * 15360);
                tma2d(sb + SM_G0, &tm_g, fc0, 0, BAR(B_GU));
                tma2d(sb + SM_U0, &tm_u, fc0, 0, BAR(B_GU));
                tma2d(sb + SM_G1, &tm_g, fc0, 192, BAR(B_GU));
                tma2d(sb + SM_U1, &tm_u, fc0, 192, BAR(B_GU));
                mbar_wait(BAR(B_OE));
                mbar_expect(BAR(B_GU), 2 * 15360);
                tma2d(sb + SM_G2, &tm_g, fc0, 384, BAR(B_GU));
                tma2d(sb + SM_U2, &tm_u, fc0, 384, BAR(B_GU));
                mbar_expect(BAR(B_DN), 36 * 1152);
            }
            __syncwarp();
            for (int r = lane; r < 36; r += 32) bulk_ld(sb + SM_DN + r * 1168, P.wd + (cta * 36 + r) * DM, 1152, BAR(B_DN));
        }
        mbar_wait(BAR(B_OE));
    }

    uint32_t mykey, key8;
    {
        const uint4* src = (const uint4*)g_ll.rkey + tid;
        uint4 k = ld_rlx16(src);
        ll_fix16(k, src);
        __syncwarp();
        const uint32_t wm = __reduce_max_sync(~0u, max(max(k.x, k.y), max(k.z, k.w)));
        uint32_t* wmax = (uint32_t*)(misc + MI_WMAX);
        if (lane == 0) wmax[warp] = wm;
        BAR_SYNC(8, 512);
        if (warp == 0) TS(25);
        const uint32_t mv = wmax[lane & 15];
        int cnt = 0;
#pragma unroll
        for (int j = 0; j < 4; j++) { const uint4 u = ((const uint4*)wmax)[j]; cnt += (u.x > mv) + (u.y > mv) + (u.z > mv) + (u.w > mv); }
        const uint32_t T = __reduce_max_sync(~0u, cnt >= 7 ? mv : 0u);
        uint32_t* cand = (uint32_t*)(misc + MI_RED);
        uint32_t* nc = (uint32_t*)(misc + MI_NC);
        if (k.x >= T) cand[atomicAdd(nc, 1)] = k.x;
        if (k.y >= T) cand[atomicAdd(nc, 1)] = k.y;
        if (k.z >= T) cand[atomicAdd(nc, 1)] = k.z;
        if (k.w >= T) cand[atomicAdd(nc, 1)] = k.w;
        BAR_SYNC(8, 512);
        const int n = *nc;
        uint32_t a = 0, b = 0;
        for (int i = lane; i < n; i += 32) {
            const uint32_t c = cand[i];
            int r = 0;
            for (int j = 0; j < n; j++) r += cand[j] > c;
            if (r == (warp >> 1)) a = c;
            if (r == 7) b = c;
        }
        __syncwarp();
        mykey = __reduce_max_sync(~0u, a); key8 = __reduce_max_sync(~0u, b);
    }
    {
        const int tok = 2047 - (mykey & 2047), tk = warp >> 1, p = (warp & 1) * 36 + lane;
        const uint4* src = (const uint4*)g_ll.h[tok] + p;
        uint4 a = ld_rlx16(src), b;
        if (lane < 4) b = ld_rlx16(src + 32);
        uint2 su = ld_rlx8(&g_ll.stat2[tok]);
        ll_fix8(su, &g_ll.stat2[tok]);
        const float inv = __uint_as_float(su.y);
        const uint32_t m2 = (su.x >> 16) * 0x10001u;
        ll_fix16(a, src);
        *(uint4*)(smem + SM_HS + tk * 1168 + p * 16) = a;
        *(uint4*)(smem + SM_HN + tk * 1168 + p * 16) = make_uint4(ln_apply(a.x, m2, inv), ln_apply(a.y, m2, inv), ln_apply(a.z, m2, inv), ln_apply(a.w, m2, inv));
        if (lane < 4) {
            ll_fix16(b, src + 32);
            *(uint4*)(smem + SM_HS + tk * 1168 + (p + 32) * 16) = b;
            *(uint4*)(smem + SM_HN + tk * 1168 + (p + 32) * 16) = make_uint4(ln_apply(b.x, m2, inv), ln_apply(b.y, m2, inv), ln_apply(b.z, m2, inv), ln_apply(b.w, m2, inv));
        }
        if (lane == 0 && (warp & 1) == 0) {
            uint32_t u = (mykey & 0xFFFFF800u) | 0x400u;
            u = (u & 0x80000000u) ? (u & 0x7FFFFFFFu) : ~u;
            const float r = bfr(__uint_as_float(u));
            ((float2*)(misc + MI_SEL))[tk] = make_float2(__int_as_float(tok), bfr(1.0f / (1.0f + __expf(-r))));
        }
    }
    BAR_SYNC(8, 512);
    if (warp == 0) TS(26);

    mbar_wait(BAR(B_GU));
    if (warp == 0) TS(27);
    if (warp < 15) {
        const int mt = warp % 5, kt = warp / 5, mat = lane >> 3, r = lane & 7;
        const uint32_t gb = kt == 0 ? SM_G0 : (kt == 1 ? SM_G1 : SM_G2);
        const uint32_t wa = sb + gb + (mat & 1) * 15360 + ((mat >> 1) * 8 + r) * 80 + mt * 16;
        const uint32_t ha = sb + SM_HN + r * 1168 + (kt * 192 + 8 * mat) * 2;
        float c0[4] = {0, 0, 0, 0}, c1[4] = {0, 0, 0, 0};
#pragma unroll
        for (int s = 0; s < 6; s++) {
            uint32_t a0[4], a1[4], b[4];
            ldsm4t(a0, wa + s * 2560); ldsm4t(a1, wa + s * 2560 + 1280); ldsm4(b, ha + s * 64);
            mma_bf16(c0, a0[0], a0[1], a0[2], a0[3], b[0], b[1]);
            mma_bf16(c1, a1[0], a1[1], a1[2], a1[3], b[2], b[3]);
        }
        ((float4*)(misc + MI_RED))[warp * 32 + lane] = make_float4(c0[0] + c1[0], c0[1] + c1[1], c0[2] + c1[2], c0[3] + c1[3]);
    }
    BAR_SYNC(8, 512);
    if (warp < 5) {
        const float4* red = (const float4*)(misc + MI_RED) + tid;
        const float4 a = red[0], b = red[160], c = red[320];
        const float g0 = bfr(a.x + b.x + c.x), g1 = bfr(a.y + b.y + c.y), u0 = bfr(a.z + b.z + c.z), u1 = bfr(a.w + b.w + c.w);
        const float y0 = bfr(g0 / (1.0f + __expf(-g0))) * u0, y1 = bfr(g1 / (1.0f + __expf(-g1))) * u1;
        const int f = 8 * warp + g - (cta & 1) * 4;
        if (f >= 0 && f < 36) {
            bf16* act = (bf16*)(misc + MI_ACT);
            act[(2 * t) * 56 + f] = __float2bfloat16_rn(y0);
            act[(2 * t + 1) * 56 + f] = __float2bfloat16_rn(y1);
        }
    }
    BAR_SYNC(8, 512);
    mbar_wait(BAR(B_DN));
    if (warp == 0) TS(28);
    {
        uint32_t b[6];
#pragma unroll
        for (int i = 0; i < 6; i++) b[i] = *(const uint32_t*)(misc + MI_ACT + g * 112 + i * 16 + t * 4);
        const int mat = lane >> 3, r = lane & 7;
#pragma unroll
        for (int it = 0; it < 3; it++) {
            const int mt = warp + 16 * it;
            if (mt < 36) {
                float c[4] = {0, 0, 0, 0};
#pragma unroll
                for (int s = 0; s < 3; s++) {
                    uint32_t a[4];
                    ldsm4t(a, sb + SM_DN + min(16 * s + (mat >> 1) * 8 + r, 35) * 1168 + (16 * mt + (mat & 1) * 8) * 2);
                    mma_bf16(c, a[0], a[1], a[2], a[3], b[2*s], b[2*s+1]);
                }
                st_rlx8(&g_ll.y[2 * mt][cta][2 * lane], nzf(c[0]), nzf(c[1]));
                st_rlx8(&g_ll.y[2 * mt + 1][cta][2 * lane], nzf(c[2]), nzf(c[3]));
            }
        }
    }
    if (warp == 0) TS(29);
    if (wg == 0) {
        const uint32_t m0 = (__float_as_uint(st0.x) >> 16) * 0x10001u, m1 = (__float_as_uint(st1.x) >> 16) * 0x10001u;
        uint32_t* po = (uint32_t*)(P.out + (qb * 64 + orow) * DM + hg * 144) + t;
#pragma unroll
        for (int b = 0; b < 18; b++) {
            if (key0 < key8) po[4 * b] = add_bf2(hw[2*b], ln_apply(hw[2*b], m0, st0.y));
            if (key1 < key8) po[8 * 288 + 4 * b] = add_bf2(hw[2*b+1], ln_apply(hw[2*b+1], m1, st1.y));
        }
    }
    if (cta < 72) {
        const uint4* src = (const uint4*)g_ll.y[cta] + tid;
        uint4 v[4];
#pragma unroll
        for (int j = 0; j < 4; j++) v[j] = ld_rlx16(src + j * 512);
        float4 s = make_float4(0, 0, 0, 0);
#pragma unroll
        for (int j = 0; j < 4; j++) {
            ll_fix16(v[j], src + j * 512);
            s.x += __uint_as_float(v[j].x); s.y += __uint_as_float(v[j].y); s.z += __uint_as_float(v[j].z); s.w += __uint_as_float(v[j].w);
        }
        __syncwarp();
        s.x += __shfl_xor_sync(~0u, s.x, 16); s.y += __shfl_xor_sync(~0u, s.y, 16);
        s.z += __shfl_xor_sync(~0u, s.z, 16); s.w += __shfl_xor_sync(~0u, s.w, 16);
        if (lane < 16) ((float4*)(misc + MI_RED))[warp * 16 + lane] = s;
        BAR_SYNC(8, 512);
        if (warp == 0) TS(30);
        if (tid < 64) {
            float y = 0.f;
#pragma unroll
            for (int w = 0; w < 16; w++) y += ((const float*)(misc + MI_RED))[w * 64 + tid];
            const int tk = tid & 7, col = cta * 8 + (tid >> 3);
            const float2 sel = ((const float2*)(misc + MI_SEL))[tk];
            const float hn = __bfloat162float(((const bf16*)(smem + SM_HN + tk * 1168))[col]);
            const float h = __bfloat162float(((const bf16*)(smem + SM_HS + tk * 1168))[col]);
            P.out[__float_as_int(sel.x) * DM + col] = __float2bfloat16_rn(h + bfr(hn + bfr(bfr(y) * sel.y)));
        }
        if (cta == 0 && tid == 0) { g_cnt[0] = 0; g_cnt[32] = 0; }
    }
    if (warp == 0) TS(31);
}

typedef CUresult (*EncodeFn)(CUtensorMap*, CUtensorMapDataType, cuuint32_t, void*, const cuuint64_t*, const cuuint64_t*,
                             const cuuint32_t*, const cuuint32_t*, CUtensorMapInterleave, CUtensorMapSwizzle,
                             CUtensorMapL2promotion, CUtensorMapFloatOOBfill);

static void make_map(EncodeFn enc, CUtensorMap* tm, const void* p, int cols, int rows, int bc, int br, CUtensorMapSwizzle sw) {
    cuuint64_t gd[2] = {(cuuint64_t)cols, (cuuint64_t)rows}, gs[1] = {(cuuint64_t)cols * 2};
    cuuint32_t bx[2] = {(cuuint32_t)bc, (cuuint32_t)br}, es[2] = {1, 1};
    enc(tm, CU_TENSOR_MAP_DATA_TYPE_BFLOAT16, 2, (void*)p, gd, gs, bx, es, CU_TENSOR_MAP_INTERLEAVE_NONE, sw,
        CU_TENSOR_MAP_L2_PROMOTION_L2_128B, CU_TENSOR_MAP_FLOAT_OOB_FILL_NONE);
}

extern "C" void kernel_launch(void* const* d_in, const int* in_sizes, int n_in, void* d_out, int out_size) {
    static EncodeFn enc = nullptr;
    if (!enc) {
        void* fn = nullptr;
        cudaDriverEntryPointQueryResult qr;
        cudaGetDriverEntryPoint("cuTensorMapEncodeTiled", &fn, cudaEnableDefault, &qr);
        enc = (EncodeFn)fn;
        cudaFuncSetAttribute(fused_block, cudaFuncAttributeMaxDynamicSharedMemorySize, SM_TOTAL);
    }
    Params P;
    P.x = (const bf16*)d_in[0]; P.wq = (const bf16*)d_in[1]; P.wk = (const bf16*)d_in[2]; P.wv = (const bf16*)d_in[3];
    P.wo = (const bf16*)d_in[4]; P.wr = (const bf16*)d_in[6]; P.wg = (const bf16*)d_in[7]; P.wu = (const bf16*)d_in[8];
    P.wd = (const bf16*)d_in[9]; P.out = (bf16*)d_out;
    CUtensorMap tx, twq, twqt, tg, tu;
    make_map(enc, &tx, P.x, DM, SEQ, 64, 64, CU_TENSOR_MAP_SWIZZLE_128B);
    make_map(enc, &twq, P.wq, DM, DM, 64, 64, CU_TENSOR_MAP_SWIZZLE_128B);
    make_map(enc, &twqt, P.wq, DM, DM, 16, 64, CU_TENSOR_MAP_SWIZZLE_32B);
    make_map(enc, &tg, P.wg, FF, DM, 40, 192, CU_TENSOR_MAP_SWIZZLE_NONE);
    make_map(enc, &tu, P.wu, FF, DM, 40, 192, CU_TENSOR_MAP_SWIZZLE_NONE);
    fused_block<<<NCTA, NTHR, SM_TOTAL, cudaStreamPerThread>>>(tx, twq, twqt, tg, tu, P);
}
```

```cpp
#include <cuda_runtime.h>
#include <cuda_bf16.h>
#include <cuda_fp16.h>
#include <cuda.h>
#include <stdint.h>

#define POLY_DEG3 1

__device__ __forceinline__ void wgz_rs_n256_f16_f16(uint32_t* d, uint32_t a0, uint32_t a1, uint32_t a2, uint32_t a3, uint64_t db) {
  asm volatile("{\n.reg .pred p;\nsetp.ne.b32 p, 0, 0;\n"
    "wgmma.mma_async.sync.aligned.m64n256k16.f16.f16.f16 "
    "{%0,%1,%2,%3,%4,%5,%6,%7,%8,%9,%10,%11,%12,%13,%14,%15,%16,%17,%18,%19,%20,%21,%22,%23,%24,%25,%26,%27,%28,%29,%30,%31,%32,%33,%34,%35,%36,%37,%38,%39,%40,%41,%42,%43,%44,%45,%46,%47,%48,%49,%50,%51,%52,%53,%54,%55,%56,%57,%58,%59,%60,%61,%62,%63}, "
    "{%64,%65,%66,%67}, %68, p, 1, 1, 0;\n}\n"
    : "=r"(d[0]), "=r"(d[1]), "=r"(d[2]), "=r"(d[3]), "=r"(d[4]), "=r"(d[5]), "=r"(d[6]), "=r"(d[7]),
      "=r"(d[8]), "=r"(d[9]), "=r"(d[10]), "=r"(d[11]), "=r"(d[12]), "=r"(d[13]), "=r"(d[14]), "=r"(d[15]),
      "=r"(d[16]), "=r"(d[17]), "=r"(d[18]), "=r"(d[19]), "=r"(d[20]), "=r"(d[21]), "=r"(d[22]), "=r"(d[23]),
      "=r"(d[24]), "=r"(d[25]), "=r"(d[26]), "=r"(d[27]), "=r"(d[28]), "=r"(d[29]), "=r"(d[30]), "=r"(d[31]),
      "=r"(d[32]), "=r"(d[33]), "=r"(d[34]), "=r"(d[35]), "=r"(d[36]), "=r"(d[37]), "=r"(d[38]), "=r"(d[39]),
      "=r"(d[40]), "=r"(d[41]), "=r"(d[42]), "=r"(d[43]), "=r"(d[44]), "=r"(d[45]), "=r"(d[46]), "=r"(d[47]),
      "=r"(d[48]), "=r"(d[49]), "=r"(d[50]), "=r"(d[51]), "=r"(d[52]), "=r"(d[53]), "=r"(d[54]), "=r"(d[55]),
      "=r"(d[56]), "=r"(d[57]), "=r"(d[58]), "=r"(d[59]), "=r"(d[60]), "=r"(d[61]), "=r"(d[62]), "=r"(d[63])
    : "r"(a0), "r"(a1), "r"(a2), "r"(a3), "l"(db));
}
__device__ __forceinline__ void wg_rs_n256_f16_f16(uint32_t* d, uint32_t a0, uint32_t a1, uint32_t a2, uint32_t a3, uint64_t db) {
  asm volatile("{\n.reg .pred p;\nsetp.ne.b32 p, 1, 0;\n"
    "wgmma.mma_async.sync.aligned.m64n256k16.f16.f16.f16 "
    "{%0,%1,%2,%3,%4,%5,%6,%7,%8,%9,%10,%11,%12,%13,%14,%15,%16,%17,%18,%19,%20,%21,%22,%23,%24,%25,%26,%27,%28,%29,%30,%31,%32,%33,%34,%35,%36,%37,%38,%39,%40,%41,%42,%43,%44,%45,%46,%47,%48,%49,%50,%51,%52,%53,%54,%55,%56,%57,%58,%59,%60,%61,%62,%63}, "
    "{%64,%65,%66,%67}, %68, p, 1, 1, 0;\n}\n"
    : "+r"(d[0]), "+r"(d[1]), "+r"(d[2]), "+r"(d[3]), "+r"(d[4]), "+r"(d[5]), "+r"(d[6]), "+r"(d[7]),
      "+r"(d[8]), "+r"(d[9]), "+r"(d[10]), "+r"(d[11]), "+r"(d[12]), "+r"(d[13]), "+r"(d[14]), "+r"(d[15]),
      "+r"(d[16]), "+r"(d[17]), "+r"(d[18]), "+r"(d[19]), "+r"(d[20]), "+r"(d[21]), "+r"(d[22]), "+r"(d[23]),
      "+r"(d[24]), "+r"(d[25]), "+r"(d[26]), "+r"(d[27]), "+r"(d[28]), "+r"(d[29]), "+r"(d[30]), "+r"(d[31]),
      "+r"(d[32]), "+r"(d[33]), "+r"(d[34]), "+r"(d[35]), "+r"(d[36]), "+r"(d[37]), "+r"(d[38]), "+r"(d[39]),
      "+r"(d[40]), "+r"(d[41]), "+r"(d[42]), "+r"(d[43]), "+r"(d[44]), "+r"(d[45]), "+r"(d[46]), "+r"(d[47]),
      "+r"(d[48]), "+r"(d[49]), "+r"(d[50]), "+r"(d[51]), "+r"(d[52]), "+r"(d[53]), "+r"(d[54]), "+r"(d[55]),
      "+r"(d[56]), "+r"(d[57]), "+r"(d[58]), "+r"(d[59]), "+r"(d[60]), "+r"(d[61]), "+r"(d[62]), "+r"(d[63])
    : "r"(a0), "r"(a1), "r"(a2), "r"(a3), "l"(db));
}
__device__ __forceinline__ void wg_rs_n24_f32_f16(float* d, uint32_t a0, uint32_t a1, uint32_t a2, uint32_t a3, uint64_t db) {
  asm volatile("{\n.reg .pred p;\nsetp.ne.b32 p, 1, 0;\n"
    "wgmma.mma_async.sync.aligned.m64n24k16.f32.f16.f16 "
    "{%0,%1,%2,%3,%4,%5,%6,%7,%8,%9,%10,%11}, "
    "{%12,%13,%14,%15}, %16, p, 1, 1, 1;\n}\n"
    : "+f"(d[0]), "+f"(d[1]), "+f"(d[2]), "+f"(d[3]), "+f"(d[4]), "+f"(d[5]), "+f"(d[6]), "+f"(d[7]),
      "+f"(d[8]), "+f"(d[9]), "+f"(d[10]), "+f"(d[11])
    : "r"(a0), "r"(a1), "r"(a2), "r"(a3), "l"(db));
}
__device__ __forceinline__ void wgz_ss_n128_f32_bf16(float* d, uint64_t da, uint64_t db) {
  asm volatile("{\n.reg .pred p;\nsetp.ne.b32 p, 0, 0;\n"
    "wgmma.mma_async.sync.aligned.m64n128k16.f32.bf16.bf16 "
    "{%0,%1,%2,%3,%4,%5,%6,%7,%8,%9,%10,%11,%12,%13,%14,%15,%16,%17,%18,%19,%20,%21,%22,%23,%24,%25,%26,%27,%28,%29,%30,%31,%32,%33,%34,%35,%36,%37,%38,%39,%40,%41,%42,%43,%44,%45,%46,%47,%48,%49,%50,%51,%52,%53,%54,%55,%56,%57,%58,%59,%60,%61,%62,%63}, "
    "%64, %65, p, 1, 1, 0, 1;\n}\n"
    : "=f"(d[0]), "=f"(d[1]), "=f"(d[2]), "=f"(d[3]), "=f"(d[4]), "=f"(d[5]), "=f"(d[6]), "=f"(d[7]),
      "=f"(d[8]), "=f"(d[9]), "=f"(d[10]), "=f"(d[11]), "=f"(d[12]), "=f"(d[13]), "=f"(d[14]), "=f"(d[15]),
      "=f"(d[16]), "=f"(d[17]), "=f"(d[18]), "=f"(d[19]), "=f"(d[20]), "=f"(d[21]), "=f"(d[22]), "=f"(d[23]),
      "=f"(d[24]), "=f"(d[25]), "=f"(d[26]), "=f"(d[27]), "=f"(d[28]), "=f"(d[29]), "=f"(d[30]), "=f"(d[31]),
      "=f"(d[32]), "=f"(d[33]), "=f"(d[34]), "=f"(d[35]), "=f"(d[36]), "=f"(d[37]), "=f"(d[38]), "=f"(d[39]),
      "=f"(d[40]), "=f"(d[41]), "=f"(d[42]), "=f"(d[43]), "=f"(d[44]), "=f"(d[45]), "=f"(d[46]), "=f"(d[47]),
      "=f"(d[48]), "=f"(d[49]), "=f"(d[50]), "=f"(d[51]), "=f"(d[52]), "=f"(d[53]), "=f"(d[54]), "=f"(d[55]),
      "=f"(d[56]), "=f"(d[57]), "=f"(d[58]), "=f"(d[59]), "=f"(d[60]), "=f"(d[61]), "=f"(d[62]), "=f"(d[63])
    : "l"(da), "l"(db));
}
__device__ __forceinline__ void wg_ss_n128_f32_bf16(float* d, uint64_t da, uint64_t db) {
  asm volatile("{\n.reg .pred p;\nsetp.ne.b32 p, 1, 0;\n"
    "wgmma.mma_async.sync.aligned.m64n128k16.f32.bf16.bf16 "
    "{%0,%1,%2,%3,%4,%5,%6,%7,%8,%9,%10,%11,%12,%13,%14,%15,%16,%17,%18,%19,%20,%21,%22,%23,%24,%25,%26,%27,%28,%29,%30,%31,%32,%33,%34,%35,%36,%37,%38,%39,%40,%41,%42,%43,%44,%45,%46,%47,%48,%49,%50,%51,%52,%53,%54,%55,%56,%57,%58,%59,%60,%61,%62,%63}, "
    "%64, %65, p, 1, 1, 0, 1;\n}\n"
    : "+f"(d[0]), "+f"(d[1]), "+f"(d[2]), "+f"(d[3]), "+f"(d[4]), "+f"(d[5]), "+f"(d[6]), "+f"(d[7]),
      "+f"(d[8]), "+f"(d[9]), "+f"(d[10]), "+f"(d[11]), "+f"(d[12]), "+f"(d[13]), "+f"(d[14]), "+f"(d[15]),
      "+f"(d[16]), "+f"(d[17]), "+f"(d[18]), "+f"(d[19]), "+f"(d[20]), "+f"(d[21]), "+f"(d[22]), "+f"(d[23]),
      "+f"(d[24]), "+f"(d[25]), "+f"(d[26]), "+f"(d[27]), "+f"(d[28]), "+f"(d[29]), "+f"(d[30]), "+f"(d[31]),
      "+f"(d[32]), "+f"(d[33]), "+f"(d[34]), "+f"(d[35]), "+f"(d[36]), "+f"(d[37]), "+f"(d[38]), "+f"(d[39]),
      "+f"(d[40]), "+f"(d[41]), "+f"(d[42]), "+f"(d[43]), "+f"(d[44]), "+f"(d[45]), "+f"(d[46]), "+f"(d[47]),
      "+f"(d[48]), "+f"(d[49]), "+f"(d[50]), "+f"(d[51]), "+f"(d[52]), "+f"(d[53]), "+f"(d[54]), "+f"(d[55]),
      "+f"(d[56]), "+f"(d[57]), "+f"(d[58]), "+f"(d[59]), "+f"(d[60]), "+f"(d[61]), "+f"(d[62]), "+f"(d[63])
    : "l"(da), "l"(db));
}
__device__ __forceinline__ void wgz_ss_n16_f32_bf16(float* d, uint64_t da, uint64_t db) {
  asm volatile("{\n.reg .pred p;\nsetp.ne.b32 p, 0, 0;\n"
    "wgmma.mma_async.sync.aligned.m64n16k16.f32.bf16.bf16 "
    "{%0,%1,%2,%3,%4,%5,%6,%7}, "
    "%8, %9, p, 1, 1, 0, 1;\n}\n"
    : "=f"(d[0]), "=f"(d[1]), "=f"(d[2]), "=f"(d[3]), "=f"(d[4]), "=f"(d[5]), "=f"(d[6]), "=f"(d[7])
    : "l"(da), "l"(db));
}
__device__ __forceinline__ void wg_ss_n16_f32_bf16(float* d, uint64_t da, uint64_t db) {
  asm volatile("{\n.reg .pred p;\nsetp.ne.b32 p, 1, 0;\n"
    "wgmma.mma_async.sync.aligned.m64n16k16.f32.bf16.bf16 "
    "{%0,%1,%2,%3,%4,%5,%6,%7}, "
    "%8, %9, p, 1, 1, 0, 1;\n}\n"
    : "+f"(d[0]), "+f"(d[1]), "+f"(d[2]), "+f"(d[3]), "+f"(d[4]), "+f"(d[5]), "+f"(d[6]), "+f"(d[7])
    : "l"(da), "l"(db));
}
__device__ __forceinline__ void wgz_ss_n144_f32_bf16(float* d, uint64_t da, uint64_t db) {
  asm volatile("{\n.reg .pred p;\nsetp.ne.b32 p, 0, 0;\n"
    "wgmma.mma_async.sync.aligned.m64n144k16.f32.bf16.bf16 "
    "{%0,%1,%2,%3,%4,%5,%6,%7,%8,%9,%10,%11,%12,%13,%14,%15,%16,%17,%18,%19,%20,%21,%22,%23,%24,%25,%26,%27,%28,%29,%30,%31,%32,%33,%34,%35,%36,%37,%38,%39,%40,%41,%42,%43,%44,%45,%46,%47,%48,%49,%50,%51,%52,%53,%54,%55,%56,%57,%58,%59,%60,%61,%62,%63,%64,%65,%66,%67,%68,%69,%70,%71}, "
    "%72, %73, p, 1, 1, 0, 1;\n}\n"
    : "=f"(d[0]), "=f"(d[1]), "=f"(d[2]), "=f"(d[3]), "=f"(d[4]), "=f"(d[5]), "=f"(d[6]), "=f"(d[7]),
      "=f"(d[8]), "=f"(d[9]), "=f"(d[10]), "=f"(d[11]), "=f"(d[12]), "=f"(d[13]), "=f"(d[14]), "=f"(d[15]),
      "=f"(d[16]), "=f"(d[17]), "=f"(d[18]), "=f"(d[19]), "=f"(d[20]), "=f"(d[21]), "=f"(d[22]), "=f"(d[23]),
      "=f"(d[24]), "=f"(d[25]), "=f"(d[26]), "=f"(d[27]), "=f"(d[28]), "=f"(d[29]), "=f"(d[30]), "=f"(d[31]),
      "=f"(d[32]), "=f"(d[33]), "=f"(d[34]), "=f"(d[35]), "=f"(d[36]), "=f"(d[37]), "=f"(d[38]), "=f"(d[39]),
      "=f"(d[40]), "=f"(d[41]), "=f"(d[42]), "=f"(d[43]), "=f"(d[44]), "=f"(d[45]), "=f"(d[46]), "=f"(d[47]),
      "=f"(d[48]), "=f"(d[49]), "=f"(d[50]), "=f"(d[51]), "=f"(d[52]), "=f"(d[53]), "=f"(d[54]), "=f"(d[55]),
      "=f"(d[56]), "=f"(d[57]), "=f"(d[58]), "=f"(d[59]), "=f"(d[60]), "=f"(d[61]), "=f"(d[62]), "=f"(d[63]),
      "=f"(d[64]), "=f"(d[65]), "=f"(d[66]), "=f"(d[67]), "=f"(d[68]), "=f"(d[69]), "=f"(d[70]), "=f"(d[71])
    : "l"(da), "l"(db));
}
__device__ __forceinline__ void wg_ss_n144_f32_bf16(float* d, uint64_t da, uint64_t db) {
  asm volatile("{\n.reg .pred p;\nsetp.ne.b32 p, 1, 0;\n"
    "wgmma.mma_async.sync.aligned.m64n144k16.f32.bf16.bf16 "
    "{%0,%1,%2,%3,%4,%5,%6,%7,%8,%9,%10,%11,%12,%13,%14,%15,%16,%17,%18,%19,%20,%21,%22,%23,%24,%25,%26,%27,%28,%29,%30,%31,%32,%33,%34,%35,%36,%37,%38,%39,%40,%41,%42,%43,%44,%45,%46,%47,%48,%49,%50,%51,%52,%53,%54,%55,%56,%57,%58,%59,%60,%61,%62,%63,%64,%65,%66,%67,%68,%69,%70,%71}, "
    "%72, %73, p, 1, 1, 0, 1;\n}\n"
    : "+f"(d[0]), "+f"(d[1]), "+f"(d[2]), "+f"(d[3]), "+f"(d[4]), "+f"(d[5]), "+f"(d[6]), "+f"(d[7]),
      "+f"(d[8]), "+f"(d[9]), "+f"(d[10]), "+f"(d[11]), "+f"(d[12]), "+f"(d[13]), "+f"(d[14]), "+f"(d[15]),
      "+f"(d[16]), "+f"(d[17]), "+f"(d[18]), "+f"(d[19]), "+f"(d[20]), "+f"(d[21]), "+f"(d[22]), "+f"(d[23]),
      "+f"(d[24]), "+f"(d[25]), "+f"(d[26]), "+f"(d[27]), "+f"(d[28]), "+f"(d[29]), "+f"(d[30]), "+f"(d[31]),
      "+f"(d[32]), "+f"(d[33]), "+f"(d[34]), "+f"(d[35]), "+f"(d[36]), "+f"(d[37]), "+f"(d[38]), "+f"(d[39]),
      "+f"(d[40]), "+f"(d[41]), "+f"(d[42]), "+f"(d[43]), "+f"(d[44]), "+f"(d[45]), "+f"(d[46]), "+f"(d[47]),
      "+f"(d[48]), "+f"(d[49]), "+f"(d[50]), "+f"(d[51]), "+f"(d[52]), "+f"(d[53]), "+f"(d[54]), "+f"(d[55]),
      "+f"(d[56]), "+f"(d[57]), "+f"(d[58]), "+f"(d[59]), "+f"(d[60]), "+f"(d[61]), "+f"(d[62]), "+f"(d[63]),
      "+f"(d[64]), "+f"(d[65]), "+f"(d[66]), "+f"(d[67]), "+f"(d[68]), "+f"(d[69]), "+f"(d[70]), "+f"(d[71])
    : "l"(da), "l"(db));
}

typedef __nv_bfloat16 bf16;
constexpr int SEQ = 2048, DM = 576, FF = 4608;
constexpr int NCTA = 128, NTHR = 512;

struct LLScratch {
    uint32_t o[32][8][2304];
    uint32_t h[SEQ][288];
    float    y[72][NCTA][64];
    float4   part[32][4][64];
    float2   stat2[SEQ];
    uint32_t rkey[SEQ];
};
static_assert(sizeof(LLScratch) % (NCTA * 16) == 0, "zero slices");
__device__ __align__(1024) LLScratch g_ll;
__device__ __align__(1024) uint4 g_kv[SEQ * 5];
__device__ __align__(1024) uint4 g_wo[4 * 36 * 288];
__device__ __align__(128) float4 g_kvraw[SEQ * 9];
__device__ __align__(128) float4 g_info[NCTA];
__device__ __align__(128) float2 g_stat1[SEQ];
__device__ __align__(128) float  g_colsum[4][DM];
__device__ __align__(128) uint32_t g_cnt[64];
constexpr uint32_t CNT1 = NCTA + 72 * 4, CNT2 = NCTA;

#define TS(i)

constexpr int SM_WQ0 = 129024;
constexpr int SM_X = 147456;
constexpr int SM_OLO = 126976, SM_OHI = 163840;
constexpr int SM_A = 200704;
constexpr int SM_XS = 27648;
constexpr int SM_G0 = 50688, SM_U0 = 66048, SM_G1 = 163840, SM_U1 = 179200, SM_G2 = 82944, SM_U2 = 98304;
constexpr int SM_DN = 113664;
constexpr int SM_HN = SM_A, SM_HS = SM_A + 9344;
constexpr int SM_MISC = 221184;
constexpr int SM_BAR = SM_MISC + 10880;
constexpr int SM_TOTAL = 232448;
constexpr int MI_STAT = 0;
constexpr int MI_CS = 512;
constexpr int MI_KP = 1088;
constexpr int MI_WMAX = 1152;
constexpr int MI_NC = 1216;
constexpr int MI_SEL = 1232;
constexpr int MI_ACT = 1312;
constexpr int MI_RED = 2304;
enum { B_FULL = 0, B_QC = 9, B_KVF = 18, B_KVD = 26, B_AUX = 32, B_ZOK, B_QRD, B_WO0, B_WO1, B_OHI, B_OHT, B_OC, B_OM, B_OE, B_GU, B_DN, B_NUM };
static_assert(B_NUM * 8 <= SM_TOTAL - SM_BAR, "barriers");

constexpr uint32_t sb = 1024;
#define BAR(i) (sb + SM_BAR + 8 * (i))

#define WG_FENCE() asm volatile("wgmma.fence.sync.aligned;" ::: "memory")
#define WG_COMMIT() asm volatile("wgmma.commit_group.sync.aligned;" ::: "memory")
#define WG_WAIT(n) asm volatile("wgmma.wait_group.sync.aligned %0;" :: "n"(n) : "memory")
#define BAR_SYNC(id, n) asm volatile("bar.sync %0, %1;" :: "n"(id), "n"(n) : "memory")
#define BAR_ARRIVE(id, n) asm volatile("bar.arrive %0, %1;" :: "n"(id), "n"(n) : "memory")
#define PROXY_FENCE() asm volatile("fence.proxy.async;" ::: "memory")
#define PROXY_FENCE_SMEM() asm volatile("fence.proxy.async.shared::cta;" ::: "memory")

__device__ __forceinline__ constexpr uint64_t mkdesc(uint32_t addr, uint32_t lbo, uint32_t sbo, uint32_t mode) {
    return (uint64_t)((addr & 0x3FFFF) >> 4) | ((uint64_t)(lbo >> 4) << 16) | ((uint64_t)(sbo >> 4) << 32) | ((uint64_t)mode << 62);
}
__device__ __forceinline__ void mbar_init(uint32_t b, int c) { asm volatile("mbarrier.init.shared::cta.b64 [%0], %1;" :: "r"(b), "r"(c) : "memory"); }
__device__ __forceinline__ void mbar_expect(uint32_t b, uint32_t tx) { asm volatile("mbarrier.arrive.expect_tx.shared::cta.b64 _, [%0], %1;" :: "r"(b), "r"(tx) : "memory"); }
__device__ __forceinline__ void mbar_arrive(uint32_t b) { asm volatile("mbarrier.arrive.shared::cta.b64 _, [%0];" :: "r"(b) : "memory"); }
__device__ __forceinline__ bool mbar_test(uint32_t b) {
    uint32_t ok;
    asm volatile("{.reg .pred p; mbarrier.test_wait.parity.shared::cta.b64 p, [%1], 0; selp.u32 %0, 1, 0, p;}" : "=r"(ok) : "r"(b) : "memory");
    return ok;
}
__device__ __forceinline__ void mbar_wait(uint32_t b) {
    asm volatile("{\n.reg .pred p;\n.reg .u32 c;\nmov.u32 c, 0;\n"
                 "W: .pragma \"nounroll\";\nmbarrier.try_wait.parity.shared::cta.b64 p, [%0], 0;\n@p bra D;\n"
                 "add.u32 c, c, 1;\nsetp.lt.u32 p, c, 0x400000;\n@p bra W;\ntrap;\nD:\n}" :: "r"(b) : "memory");
}
__device__ __forceinline__ void bulk_ld(uint32_t dst, const void* src, uint32_t bytes, uint32_t bar) {
    asm volatile("cp.async.bulk.shared::cluster.global.mbarrier::complete_tx::bytes [%0], [%1], %2, [%3];"
                 :: "r"(dst), "l"(src), "r"(bytes), "r"(bar) : "memory");
}
__device__ __forceinline__ void tma2d(uint32_t dst, const CUtensorMap* tm, int c0, int c1, uint32_t bar) {
    asm volatile("cp.async.bulk.tensor.2d.shared::cluster.global.mbarrier::complete_tx::bytes [%0], [%1, {%3, %4}], [%2];"
                 :: "r"(dst), "l"(tm), "r"(bar), "r"(c0), "r"(c1) : "memory");
}
__device__ __forceinline__ void l2_prefetch(const void* src, uint32_t bytes) {
    asm volatile("cp.async.bulk.prefetch.L2.global [%0], %1;" :: "l"(src), "r"(bytes) : "memory");
}
__device__ __forceinline__ void red_release(uint32_t* p) { asm volatile("red.release.gpu.global.add.u32 [%0], 1;" :: "l"(p) : "memory"); }
__device__ __forceinline__ void poll_counter(const uint32_t* p, uint32_t target) {
    asm volatile("{\n.reg .pred p;\n.reg .u32 c, v;\nmov.u32 c, 0;\n"
                 "W: .pragma \"nounroll\";\nld.acquire.gpu.global.u32 v, [%0];\nsetp.ge.u32 p, v, %1;\n@p bra D;\n"
                 "add.u32 c, c, 1;\nsetp.lt.u32 p, c, 0x400000;\n@p bra W;\ntrap;\nD:\n}" :: "l"(p), "r"(target) : "memory");
}
__device__ __forceinline__ uint4 ld_rlx16(const void* p) {
    uint4 v;
    asm volatile("ld.relaxed.gpu.global.v4.u32 {%0,%1,%2,%3}, [%4];" : "=r"(v.x), "=r"(v.y), "=r"(v.z), "=r"(v.w) : "l"(p) : "memory");
    return v;
}
__device__ __forceinline__ uint2 ld_rlx8(const void* p) {
    uint2 v;
    asm volatile("ld.relaxed.gpu.global.v2.u32 {%0,%1}, [%2];" : "=r"(v.x), "=r"(v.y) : "l"(p) : "memory");
    return v;
}
__device__ __forceinline__ bool ll_ok(const uint4& v) { return v.x != 0 && v.y != 0 && v.z != 0 && v.w != 0; }
__device__ __forceinline__ void ll_fix16(uint4& v, const void* p) {
    asm volatile("{\n.reg .pred p;\n.reg .u32 c, m;\nmov.u32 c, 0;\n"
                 "W: .pragma \"nounroll\";\nmin.u32 m, %0, %1;\nmin.u32 m, m, %2;\nmin.u32 m, m, %3;\nsetp.ne.u32 p, m, 0;\n@p bra D;\n"
                 "ld.relaxed.gpu.global.v4.u32 {%0,%1,%2,%3}, [%4];\n"
                 "add.u32 c, c, 1;\nsetp.lt.u32 p, c, 0x400000;\n@p bra W;\ntrap;\nD:\n}"
                 : "+r"(v.x), "+r"(v.y), "+r"(v.z), "+r"(v.w) : "l"(p) : "memory");
}
__device__ __forceinline__ void ll_fix8(uint2& v, const void* p) {
    asm volatile("{\n.reg .pred p;\n.reg .u32 c, m;\nmov.u32 c, 0;\n"
                 "W: .pragma \"nounroll\";\nmin.u32 m, %0, %1;\nsetp.ne.u32 p, m, 0;\n@p bra D;\n"
                 "ld.relaxed.gpu.global.v2.u32 {%0,%1}, [%2];\n"
                 "add.u32 c, c, 1;\nsetp.lt.u32 p, c, 0x400000;\n@p bra W;\ntrap;\nD:\n}"
                 : "+r"(v.x), "+r"(v.y) : "l"(p) : "memory");
}
__device__ __forceinline__ void st_rlx4(void* p, uint32_t a) { asm volatile("st.relaxed.gpu.global.u32 [%0], %1;" :: "l"(p), "r"(a) : "memory"); }
__device__ __forceinline__ void st_rlx8(void* p, uint32_t a, uint32_t b) { asm volatile("st.relaxed.gpu.global.v2.u32 [%0], {%1,%2};" :: "l"(p), "r"(a), "r"(b) : "memory"); }
__device__ __forceinline__ void st_rlx16(void* p, uint32_t a, uint32_t b, uint32_t c, uint32_t d) {
    asm volatile("st.relaxed.gpu.global.v4.u32 [%0], {%1,%2,%3,%4};" :: "l"(p), "r"(a), "r"(b), "r"(c), "r"(d) : "memory");
}
__device__ __forceinline__ uint32_t nz(uint32_t w) { return max(w, 1u); }
__device__ __forceinline__ uint32_t nzf(float f) { return max(__float_as_uint(f), 1u); }
__device__ __forceinline__ void mma_bf16(float* d, uint32_t a0, uint32_t a1, uint32_t a2, uint32_t a3, uint32_t b0, uint32_t b1) {
    asm volatile("mma.sync.aligned.m16n8k16.row.col.f32.bf16.bf16.f32 {%0,%1,%2,%3}, {%4,%5,%6,%7}, {%8,%9}, {%0,%1,%2,%3};"
                 : "+f"(d[0]), "+f"(d[1]), "+f"(d[2]), "+f"(d[3]) : "r"(a0), "r"(a1), "r"(a2), "r"(a3), "r"(b0), "r"(b1));
}
__device__ __forceinline__ void ldsm4(uint32_t* r, uint32_t a) {
    asm volatile("ldmatrix.sync.aligned.m8n8.x4.shared.b16 {%0,%1,%2,%3}, [%4];" : "=r"(r[0]), "=r"(r[1]), "=r"(r[2]), "=r"(r[3]) : "r"(a) : "memory");
}
__device__ __forceinline__ void ldsm4t(uint32_t* r, uint32_t a) {
    asm volatile("ldmatrix.sync.aligned.m8n8.x4.trans.shared.b16 {%0,%1,%2,%3}, [%4];" : "=r"(r[0]), "=r"(r[1]), "=r"(r[2]), "=r"(r[3]) : "r"(a) : "memory");
}
__device__ __forceinline__ float frcp(float x) { float r; asm("rcp.approx.ftz.f32 %0, %1;" : "=f"(r) : "f"(x)); return r; }
__device__ __forceinline__ float fsqrt(float x) { float r; asm("sqrt.approx.ftz.f32 %0, %1;" : "=f"(r) : "f"(x)); return r; }
__device__ __forceinline__ float bfr(float x) { return __bfloat162float(__float2bfloat16_rn(x)); }
__device__ __forceinline__ uint32_t pk_bf(float lo, float hi) { uint32_t r; asm("cvt.rn.bf16x2.f32 %0, %1, %2;" : "=r"(r) : "f"(hi), "f"(lo)); return r; }
__device__ __forceinline__ uint32_t pk_h(float lo, float hi) { uint32_t r; asm("cvt.rn.f16x2.f32 %0, %1, %2;" : "=r"(r) : "f"(hi), "f"(lo)); return r; }
__device__ __forceinline__ float bf_lo(uint32_t w) { return __uint_as_float(w << 16); }
__device__ __forceinline__ float bf_hi(uint32_t w) { return __uint_as_float(w & 0xFFFF0000u); }
__device__ __forceinline__ uint32_t add_bf2(uint32_t a, uint32_t b) { uint32_t r; asm("add.rn.bf16x2 %0, %1, %2;" : "=r"(r) : "r"(a), "r"(b)); return r; }
__device__ __forceinline__ uint32_t sub_bf2(uint32_t a, uint32_t b) { uint32_t r; asm("sub.rn.bf16x2 %0, %1, %2;" : "=r"(r) : "r"(a), "r"(b)); return r; }
__device__ __forceinline__ float sq_h2(uint32_t w) { float2 f = __half22float2(*(__half2*)&w); return f.x * f.x + f.y * f.y; }
__device__ __forceinline__ float2 ln_stats(float sx, float sxx) {
    float mean = sx * (1.0f / DM);
    float var = fmaxf(sxx * (1.0f / DM) - mean * mean, 0.0f);
    float s = bfr(fsqrt(bfr(bfr(var) + 1e-5f)));
    return make_float2(bfr(mean), frcp(s));
}
__device__ __forceinline__ uint32_t ln_apply(uint32_t w, uint32_t m2, float inv) {
    uint32_t d = sub_bf2(w, m2);
    return pk_bf(bf_lo(d) * inv, bf_hi(d) * inv);
}

__device__ __forceinline__ uint32_t ex2_mufu(uint32_t v) { uint32_t r; asm("ex2.approx.f16x2 %0, %1;" : "=r"(r) : "r"(v)); return r; }
__device__ __forceinline__ uint32_t hfma2(uint32_t a, uint32_t b, uint32_t c) { uint32_t r; asm("fma.rn.f16x2 %0, %1, %2, %3;" : "=r"(r) : "r"(a), "r"(b), "r"(c)); return r; }
__device__ __forceinline__ uint32_t ex2_poly(uint32_t w, uint32_t cz, uint32_t ca) {
    uint32_t z;
    asm("lop3.b32 %0, %1, 0x003F003F, %2, 0xEA;" : "=r"(z) : "r"(w), "r"(cz));
    uint32_t g = hfma2(z, ca, 0xD1B5D1B5u);
    uint32_t q = hfma2(g, g, 0xDAB6DAB6u);
    uint32_t h = hfma2(q, q, 0x7BA87BA8u);
    return __funnelshift_l(w, w, 4) + h;
}
constexpr uint32_t POLY_CZ = 0x3C003C00u, POLY_CA = 0x534C534Cu;

struct Params {
    const bf16 *x, *wq, *wk, *wv, *wo, *wr, *wg, *wu, *wd;
    bf16* out;
};

__device__ __noinline__ void attn_safe(const bf16* x, const bf16* wq, int row0, int head, uint32_t* res) {
    const int lane = threadIdx.x & 31, half = lane & 1, row = row0 + (lane >> 1);
    const float2 st = __ldcg(&g_stat1[row]);
    float q[18];
#pragma unroll
    for (int d = 0; d < 18; d++) q[d] = 0.f;
#pragma unroll 1
    for (int i = half * 288; i < half * 288 + 288; i++) {
        float xn = bfr(bfr(__bfloat162float(x[row * DM + i]) - st.x) * st.y);
#pragma unroll
        for (int d = 0; d < 18; d++) q[d] += xn * __bfloat162float(wq[i * DM + head * 18 + d]);
    }
#pragma unroll
    for (int d = 0; d < 18; d++) q[d] = bfr(q[d] + __shfl_xor_sync(~0u, q[d], 1)) * 0.23570226039551584f;
    float o[18], l = 0.f, m = -INFINITY;
#pragma unroll
    for (int d = 0; d < 18; d++) o[d] = 0.f;
#pragma unroll 1
    for (int pass = 0; pass < 2; pass++) {
#pragma unroll 1
        for (int k = half * 1024; k < half * 1024 + 1024; k++) {
            const float4* p = g_kvraw + k * 9;
            float4 e = __ldcg(p + 8);
            float s = q[16] * e.x + q[17] * e.y;
#pragma unroll
            for (int j = 0; j < 4; j++) { float4 a = __ldcg(p + j); s += q[4*j] * a.x + q[4*j+1] * a.y + q[4*j+2] * a.z + q[4*j+3] * a.w; }
            if (pass == 0) { m = fmaxf(m, s); }
            else {
                float pr = __expf(s - m);
                l += pr; o[16] += pr * e.z; o[17] += pr * e.w;
#pragma unroll
                for (int j = 0; j < 4; j++) { float4 a = __ldcg(p + 4 + j); o[4*j] += pr * a.x; o[4*j+1] += pr * a.y; o[4*j+2] += pr * a.z; o[4*j+3] += pr * a.w; }
            }
        }
        if (pass == 0) m = fmaxf(m, __shfl_xor_sync(~0u, m, 1));
    }
    l += __shfl_xor_sync(~0u, l, 1);
    const float inv = frcp(l);
    const int g = lane >> 2, t = lane & 3;
#pragma unroll
    for (int p = 0; p < 9; p++) {
        float a = o[2*p] + __shfl_xor_sync(~0u, o[2*p], 1), b = o[2*p+1] + __shfl_xor_sync(~0u, o[2*p+1], 1);
        uint32_t w = pk_bf(a * inv, b * inv);
        uint32_t v0 = __shfl_sync(~0u, w, 2 * g), v1 = __shfl_sync(~0u, w, 2 * g + 16);
        if (p == t) { res[2] = v0; res[3] = v1; }
        if (p == t + 4) { res[4] = v0; res[5] = v1; }
        if (p == 8) { res[0] = v0; res[1] = v1; }
    }
}

__device__ __noinline__ int side_job(const Params& P, int rnd, int jj, int wo_next) {
    extern __shared__ __align__(1024) uint8_t smem[];
    const int tid = threadIdx.x, lane = tid & 31, warp = tid >> 5;
    const int cta = blockIdx.x, qb = cta >> 2, hg = cta & 3;
    if (rnd == 0) {
        if (warp == 8) {
            if (lane == 0) { poll_counter(&g_cnt[32], CNT2); mbar_arrive(BAR(B_ZOK)); }
        } else if (jj == 1) {
            if (lane < 12) {
                const bf16* w = lane < 4 ? P.wg : (lane < 8 ? P.wu : P.wd);
                l2_prefetch(w + cta * 20736 + (lane & 3) * 5184, 10368);
            }
        } else {
            asm volatile("cp.async.bulk.wait_group 0;" ::: "memory");
            PROXY_FENCE();
            __syncwarp();
            if (lane == 0) red_release(&g_cnt[32]);
        }
    } else {
        if (jj < 6 && lane == 0) mbar_arrive(BAR(B_KVD + jj));
        if (warp == 12 && lane == 0) {
            if (jj == 0) PROXY_FENCE();
            if (jj == 3) {
                mbar_expect(BAR(B_OHT), 3 * 9216);
                for (int u = 1; u < 4; u++) bulk_ld(sb + SM_OHI + u * 9216, g_ll.o[qb][(hg + u) & 3], 9216, BAR(B_OHT));
            }
#pragma unroll 1
            while (wo_next < 6) {
                const uint32_t wb = wo_next < 0 ? BAR(B_QRD) : BAR(B_KVD + wo_next);
                if (jj == 7) mbar_wait(wb); else if (wo_next >= jj || !mbar_test(wb)) break;
                const int s0 = wo_next < 0 ? 26 : wo_next * 40 / 9, s1 = wo_next < 0 ? 30 : (wo_next + 1) * 40 / 9;
                mbar_expect(BAR(B_WO0), (s1 - s0) * 4608);
                bulk_ld(sb + (wo_next < 0 ? SM_A : s0 * 4608), g_wo + hg * 10368 + s0 * 288, (s1 - s0) * 4608, BAR(B_WO0));
                wo_next++;
            }
        }
        if (jj == 6) {
            mbar_wait(BAR(B_OHT));
#pragma unroll 1
            for (int i = 576 + tid; i < 2304; i += 512) {
                uint4* p = (uint4*)(smem + SM_OHI) + i;
                uint4 v = *p;
                if (!ll_ok(v)) { ll_fix16(v, (const uint4*)g_ll.o[qb][(hg + i / 576) & 3] + i % 576); *p = v; }
            }
            PROXY_FENCE_SMEM();
            __syncwarp();
            if (lane == 0) mbar_arrive(BAR(B_OHI));
        }
    }
    __syncwarp();
    return wo_next;
}

__global__ void __launch_bounds__(NTHR, 1)
fused_block(const __grid_constant__ CUtensorMap tm_x, const __grid_constant__ CUtensorMap tm_wq,
            const __grid_constant__ CUtensorMap tm_wqt, const __grid_constant__ CUtensorMap tm_g,
            const __grid_constant__ CUtensorMap tm_u, const __grid_constant__ Params P) {
    extern __shared__ __align__(1024) uint8_t smem[];
    const int tid = threadIdx.x, lane = tid & 31;
    const int warp = __shfl_sync(~0u, tid >> 5, 0);
    const int cta = blockIdx.x, qb = cta >> 2, hg = cta & 3;
    const int g = lane >> 2, t = lane & 3;
    uint8_t* const misc = smem + SM_MISC;

    const int wg = warp >> 2, wq4 = warp & 3;
    if (wg == 0) {
        if (warp == 0) TS(0);
        if (tid < B_NUM) {
            if ((uint32_t)__cvta_generic_to_shared(smem) != sb) __trap();
            const int cnt = tid < B_KVF ? 4 : (tid < B_KVD ? 1 : (tid < B_AUX || tid == B_QRD ? 16 :
                            (tid == B_WO0 ? 7 : (tid == B_OHI ? 32 : (tid >= B_OC && tid <= B_OE ? 4 : (tid == B_GU ? 2 : 1))))));
            mbar_init(BAR(tid), cnt);
            asm volatile("fence.mbarrier_init.release.cluster;" ::: "memory");
        }
        BAR_SYNC(9, 128);
        const CUtensorMap* const mytm = warp == 0 ? &tm_x : (warp == 3 ? &tm_wqt : &tm_wq);
        const uint32_t mybytes = warp == 3 ? 2048 : 8192;
        if (lane == 0) {
#pragma unroll 1
            for (int c = 0; c < (warp == 0 ? 9 : 8); c++) {
                mbar_expect(BAR(B_FULL + c), mybytes);
                if (warp == 0) tma2d(sb + SM_X + c * 8192, mytm, c * 64, qb * 64, BAR(B_FULL + c));
                else tma2d(sb + (c == 0 ? SM_WQ0 : (c - 1) * 18432) + (warp - 1) * 8192, mytm, hg * 144 + (warp - 1) * 64, c * 64, BAR(B_FULL + c));
            }
        }
        __syncwarp();
        BAR_ARRIVE(1, NTHR);
        if (cta < 72) {
            uint4 v[5];
#pragma unroll
            for (int j = 0; j < 5; j++) {
                const int k = tid + 128 * j;
                v[j] = (j < 4 || tid < 64) ? __ldg((const uint4*)(P.wq + k * DM + cta * 8)) : make_uint4(0, 0, 0, 0);
            }
            float s[8];
#pragma unroll
            for (int i = 0; i < 8; i++) s[i] = 0.f;
#pragma unroll
            for (int j = 0; j < 5; j++) {
                s[0] += bf_lo(v[j].x); s[1] += bf_hi(v[j].x); s[2] += bf_lo(v[j].y); s[3] += bf_hi(v[j].y);
                s[4] += bf_lo(v[j].z); s[5] += bf_hi(v[j].z); s[6] += bf_lo(v[j].w); s[7] += bf_hi(v[j].w);
            }
            const bool u4 = lane & 16, u2 = lane & 8, u1 = lane & 4;
#pragma unroll
            for (int i = 0; i < 4; i++) s[i] = (u4 ? s[i + 4] : s[i]) + __shfl_xor_sync(~0u, u4 ? s[i] : s[i + 4], 16);
#pragma unroll
            for (int i = 0; i < 2; i++) s[i] = (u2 ? s[i + 2] : s[i]) + __shfl_xor_sync(~0u, u2 ? s[i] : s[i + 2], 8);
            s[0] = (u1 ? s[1] : s[0]) + __shfl_xor_sync(~0u, u1 ? s[0] : s[1], 4);
            s[0] += __shfl_xor_sync(~0u, s[0], 2);
            s[0] += __shfl_xor_sync(~0u, s[0], 1);
            if (t == 0) g_colsum[warp][cta * 8 + g] = s[0];
            __syncwarp();
            if (lane == 0) red_release(&g_cnt[0]);
        }
        float acc[72];
#pragma unroll
        for (int c = 0; c < 9; c++) {
            const uint32_t slot = sb + ((c == 0 || c == 8) ? SM_WQ0 : (c - 1) * 18432);
            if (c == 2 && warp != 0 && lane == 0) {
                mbar_wait(BAR(B_QC + 0));
                mbar_expect(BAR(B_FULL + 8), mybytes);
                tma2d(sb + SM_WQ0 + (warp - 1) * 8192, mytm, hg * 144 + (warp - 1) * 64, 512, BAR(B_FULL + 8));
            }
            mbar_wait(BAR(B_FULL + c));
            if (c == 0) TS(8);
            WG_FENCE();
#pragma unroll
            for (int s = 0; s < 4; s++) {
                const uint64_t da = mkdesc(sb + SM_X + c * 8192 + s * 32, 16, 1024, 1);
                const uint64_t db = mkdesc(slot + s * 2048, 8192, 1024, 1);
                const uint64_t dt = mkdesc(slot + 16384 + s * 512, 256, 256, 3);
                if (c == 0 && s == 0) { wgz_ss_n128_f32_bf16(acc, da, db); wgz_ss_n16_f32_bf16(acc + 64, da, dt); }
                else { wg_ss_n128_f32_bf16(acc, da, db); wg_ss_n16_f32_bf16(acc + 64, da, dt); }
            }
            WG_COMMIT();
            if (c > 0) { WG_WAIT(1); if (lane == 0) mbar_arrive(BAR(B_QC + c - 1)); }
        }
        WG_WAIT(0);
        if (lane == 0) mbar_arrive(BAR(B_QC + 8));
#pragma unroll
        for (int i = 0; i < 72; i++) asm volatile("" : "+f"(acc[i]) :: "memory");
        TS(9);
        mbar_wait(BAR(B_QC + 8));
        mbar_wait(BAR(B_AUX));
        TS(10);
        const float kq = 0.23570226039551584f * 1.4426950408889634f / 512.0f;
        const float2 s0 = ((const float2*)(misc + MI_STAT))[wq4 * 16 + g], s1 = ((const float2*)(misc + MI_STAT))[wq4 * 16 + g + 8];
        const float a0 = s0.y * kq, a1 = s1.y * kq, b0 = -s0.x * a0, b1 = -s1.x * a1;
        uint8_t* qs = smem + SM_A + (wq4 * 16 + g) * 304 + t * 4;
#pragma unroll
        for (int b = 0; b < 18; b++) {
            const float2 cs = ((const float2*)(misc + MI_CS))[4 * b + t];
            *(uint32_t*)(qs + b * 16) = pk_h(fmaf(acc[4*b], a0, cs.x * b0), fmaf(acc[4*b+1], a0, cs.y * b0));
            *(uint32_t*)(qs + 8 * 304 + b * 16) = pk_h(fmaf(acc[4*b+2], a1, cs.x * b1), fmaf(acc[4*b+3], a1, cs.y * b1));
        }
    } else {
        const int wi = warp - 4, kp = wi / 3, set = wi % 3, R0 = cta * 16;
        float* const pp = (float*)misc;
        {
            const int kb = 144 * kp + 36 * t;
            uint2 xa[9], xb[9];
            uint32_t w[36];
            const bf16* wsrc = set == 0 ? P.wk + 2 * g : (set == 1 ? P.wv + 2 * g : (g == 0 ? P.wk + 16 : P.wv + 16));
#pragma unroll
            for (int s = 0; s < 9; s++) {
                xa[s] = __ldg((const uint2*)(P.x + (R0 + g) * DM + kb + 4 * s));
                xb[s] = __ldg((const uint2*)(P.x + (R0 + g + 8) * DM + kb + 4 * s));
            }
#pragma unroll
            for (int i = 0; i < 36; i++) w[i] = (set < 2 || g < 2) ? __ldg((const uint32_t*)(wsrc + (kb + i) * 18)) : 0x3F803F80u;
            float ae[4] = {0, 0, 0, 0}, ao[4] = {0, 0, 0, 0}, ce[4] = {0, 0, 0, 0}, co[4] = {0, 0, 0, 0}, g1[4] = {0, 0, 0, 0}, g2[4] = {0, 0, 0, 0};
            const uint32_t one = 0x3F803F80u;
#pragma unroll
            for (int s = 0; s < 9; s++) {
                const uint32_t e0 = __byte_perm(w[4*s], w[4*s+1], 0x5410), e1 = __byte_perm(w[4*s+2], w[4*s+3], 0x5410);
                const uint32_t o0 = __byte_perm(w[4*s], w[4*s+1], 0x7632), o1 = __byte_perm(w[4*s+2], w[4*s+3], 0x7632);
                mma_bf16(ae, xa[s].x, xb[s].x, xa[s].y, xb[s].y, e0, e1);
                mma_bf16(ao, xa[s].x, xb[s].x, xa[s].y, xb[s].y, o0, o1);
                mma_bf16(ce, one, one, one, one, e0, e1);
                mma_bf16(co, one, one, one, one, o0, o1);
                if (set == 2) {
                    mma_bf16(g1, xa[s].x, xb[s].x, xa[s].y, xb[s].y, xa[s].x, xa[s].y);
                    mma_bf16(g2, xa[s].x, xb[s].x, xa[s].y, xb[s].y, xb[s].x, xb[s].y);
                }
            }
            float* pk = pp + kp * 680;
            if (set < 2 || t == 0) {
                const int col = set * 16 + 4 * t;
                *(float4*)(pk + g * 40 + col) = make_float4(ae[0], ao[0], ae[1], ao[1]);
                *(float4*)(pk + (g + 8) * 40 + col) = make_float4(ae[2], ao[2], ae[3], ao[3]);
                if (g == 0) *(float4*)(pk + 640 + col) = make_float4(ce[0], co[0], ce[1], co[1]);
            }
            if (set == 2) {
                if (t == 1) { pk[g * 40 + 36] = ae[0]; pk[(g + 8) * 40 + 36] = ae[2]; }
                if (t == (g >> 1)) { pk[g * 40 + 38] = (g & 1) ? g1[1] : g1[0]; pk[(g + 8) * 40 + 38] = (g & 1) ? g2[3] : g2[2]; }
            }
        }
        if (wi == 0) TS(12);
        BAR_SYNC(1, NTHR);
        if (wi < 8) {
            const int r = 2 * wi + (lane >> 4), l = lane & 15, lc = min(l, 8);
            float4 a = make_float4(0, 0, 0, 0), cs = a;
            float sx = 0.f, sxx = 0.f;
#pragma unroll
            for (int k = 0; k < 4; k++) {
                const float4 u = *(const float4*)(pp + k * 680 + r * 40 + 4 * lc), v = *(const float4*)(pp + k * 680 + 640 + 4 * lc);
                a.x += u.x; a.y += u.y; a.z += u.z; a.w += u.w; cs.x += v.x; cs.y += v.y; cs.z += v.z; cs.w += v.w;
                sx += pp[k * 680 + r * 40 + 36]; sxx += pp[k * 680 + r * 40 + 38];
            }
            const float2 st = ln_stats(sx, sxx);
            a.x = bfr((a.x - st.x * cs.x) * st.y); a.y = bfr((a.y - st.x * cs.y) * st.y);
            a.z = bfr((a.z - st.x * cs.z) * st.y); a.w = bfr((a.w - st.x * cs.w) * st.y);
            float n2 = (l < 4 || l == 8) ? a.x * a.x + a.y * a.y : 0.f;
            if (l < 4) n2 += a.z * a.z + a.w * a.w;
            uint32_t vm = l >= 4 ? max(__float_as_uint(fabsf(a.z)), __float_as_uint(fabsf(a.w))) : 0u;
            if (l >= 4 && l < 8) vm = max(vm, max(__float_as_uint(fabsf(a.x)), __float_as_uint(fabsf(a.y))));
#pragma unroll
            for (int d = 1; d < 16; d <<= 1) { n2 += __shfl_xor_sync(~0u, n2, d); vm = max(vm, __shfl_xor_sync(~0u, vm, d)); }
            if (l < 9) g_kvraw[(R0 + r) * 9 + l] = a;
            if (l == 0) { pp[r * 40 + 39] = n2; pp[r * 40 + 37] = __uint_as_float(vm); }
            BAR_SYNC(3, 256);
            const uint32_t mine = __float_as_uint(n2), other = __float_as_uint(pp[l * 40 + 39]);
            const uint32_t bal = __ballot_sync(~0u, other > mine || (other == mine && l < r));
            const int rank = __popc((bal >> (lane & 16)) & 0xFFFFu);
            const int pj = rank >> 1, blk = pj == 0 ? 0 : (pj == 1 ? 4 : (pj < 5 ? pj - 1 : pj));
            const bool mu = rank < 4;
            const float ks = mu ? 512.f : (1.f / 512.f), vs = mu ? 128.f : -1.f;
            uint8_t* stg = misc + 5440 + blk * 160 + (rank & 1) * 16;
            if (l < 8) {
                const float sc = l < 4 ? ks : vs;
                *(uint2*)(stg + (l < 4 ? (l >> 1) : 3 + ((l - 4) >> 1)) * 32 + (l & 1) * 8) = make_uint2(pk_h(a.x * sc, a.y * sc), pk_h(a.z * sc, a.w * sc));
            } else if (l == 8) {
                *(uint4*)(stg + 64) = make_uint4(pk_h(a.x * ks, a.y * ks), pk_h(mu ? -3072.f : (17.f / 512.f), vs), 0u, pk_h(a.z * vs, a.w * vs));
            } else if (l == 9) {
                ((float2*)(misc + 6720))[r] = st;
                if (rank == 0) *(float*)(misc + 6852) = n2;
                if (rank == 4) *(float*)(misc + 6848) = n2;
            }
            BAR_SYNC(4, 256);
            if (wi == 0) {
#pragma unroll
                for (int it = 0; it < 3; it++) {
                    const int i = lane + 32 * it;
                    if (i < 80) g_kv[(qb * 8 + i / 10) * 40 + ((i % 10) >> 1) * 8 + 2 * hg + (i & 1)] = ((const uint4*)(misc + 5440))[i];
                }
                if (lane < 8) ((float4*)(g_stat1 + R0))[lane] = ((const float4*)(misc + 6720))[lane];
                const uint32_t vmx = __reduce_max_sync(~0u, __float_as_uint(pp[l * 40 + 37]));
                if (lane == 0) g_info[cta] = make_float4(*(float*)(misc + 6848), *(float*)(misc + 6852), __uint_as_float(vmx), 0.f);
                __syncwarp();
                if (lane == 0) red_release(&g_cnt[0]);
                TS(13);
            }
        } else if (wi == 8) {
            if (lane == 0) {
                poll_counter(&g_cnt[0], CNT1);
                PROXY_FENCE();
                for (int j = 0; j < 2; j++) {
                    mbar_wait(BAR(B_QC + j + 2));
                    mbar_expect(BAR(B_KVF + j), 20480);
                    bulk_ld(sb + j * 20480, g_kv + j * 1280, 20480, BAR(B_KVF + j));
                }
            }
            __syncwarp();
            TS(1);
            float4 st = __ldcg((const float4*)(g_stat1 + qb * 64) + lane);
            float4 c0[4], c1[4], inf[4];
#pragma unroll
            for (int j = 0; j < 4; j++) {
                c0[j] = __ldcg((const float4*)(g_colsum[j] + hg * 144) + lane);
                if (lane < 4) c1[j] = __ldcg((const float4*)(g_colsum[j] + hg * 144) + 32 + lane);
                inf[j] = __ldcg(g_info + 4 * lane + j);
            }
#pragma unroll 1
            for (int i = lane; i < (10880 - MI_NC) / 16; i += 32) ((uint4*)(misc + MI_NC))[i] = make_uint4(0, 0, 0, 0);
            ((float4*)(misc + MI_STAT))[lane] = st;
            ((float4*)(misc + MI_CS))[lane] = make_float4((c0[0].x + c0[1].x) + (c0[2].x + c0[3].x), (c0[0].y + c0[1].y) + (c0[2].y + c0[3].y),
                                                         (c0[0].z + c0[1].z) + (c0[2].z + c0[3].z), (c0[0].w + c0[1].w) + (c0[2].w + c0[3].w));
            if (lane < 4)
                ((float4*)(misc + MI_CS))[32 + lane] = make_float4((c1[0].x + c1[1].x) + (c1[2].x + c1[3].x), (c1[0].y + c1[1].y) + (c1[2].y + c1[3].y),
                                                                  (c1[0].z + c1[1].z) + (c1[2].z + c1[3].z), (c1[0].w + c1[1].w) + (c1[2].w + c1[3].w));
            uint32_t kp2 = 0, ka = 0, vm = 0;
#pragma unroll
            for (int j = 0; j < 4; j++) {
                kp2 = max(kp2, __float_as_uint(inf[j].x)); ka = max(ka, __float_as_uint(inf[j].y)); vm = max(vm, __float_as_uint(inf[j].z));
            }
            kp2 = max(kp2, __shfl_xor_sync(~0u, kp2, 1)); kp2 = max(kp2, __shfl_xor_sync(~0u, kp2, 2));
            ka = __reduce_max_sync(~0u, ka); vm = __reduce_max_sync(~0u, vm);
            uint32_t* kpp = (uint32_t*)(misc + MI_KP);
            if (t == 0) kpp[g] = kp2;
            if (lane == 0) { kpp[8] = ka; kpp[9] = vm; kpp[10] = 0; }
            PROXY_FENCE_SMEM();
            __syncwarp();
            if (lane == 0) {
                mbar_arrive(BAR(B_AUX));
#pragma unroll 1
                for (int j = 2; j < 8; j++) {
                    mbar_wait(BAR(B_QC + min(j + 2, 8)));
                    mbar_expect(BAR(B_KVF + j), 20480);
                    bulk_ld(sb + j * 20480, g_kv + j * 1280, 20480, BAR(B_KVF + j));
                }
            }
            __syncwarp();
            TS(2);
        } else {
            uint4 v[4];
#pragma unroll
            for (int it = 0; it < 4; it++) {
                const int l = tid - 416 + 96 * it;
                if (l < 324) {
                    const int i = cta * 324 + l, h2 = i / 10368, rem = i % 10368, ci = rem / 144, c = (rem % 144) >> 3, j = rem & 7;
                    const int r = ci / 36, cc = ci % 36;
                    const int k = 144 * ((h2 + cc / 9) & 3) + 72 * r + 8 * (cc % 9) + j;
                    v[it] = __ldg((const uint4*)(P.wo + k * DM + h2 * 144 + c * 8));
                }
            }
#pragma unroll
            for (int it = 0; it < 4; it++) { const int l = tid - 416 + 96 * it; if (l < 324) g_wo[cta * 324 + l] = v[it]; }
        }
    }
    BAR_SYNC(5, 512);
    if (warp == 0) TS(11);
    if (warp == 4) {
        constexpr int ZB = sizeof(LLScratch) / NCTA;
        if (lane < 7) {
            const int off = lane * 8192, n = min(8192, ZB - off);
            asm volatile("cp.async.bulk.global.shared::cta.bulk_group [%0], [%1], %2;"
                         :: "l"((uint8_t*)&g_ll + cta * ZB + off), "r"(sb + SM_MISC + MI_RED), "r"(n) : "memory");
            asm volatile("cp.async.bulk.commit_group;" ::: "memory");
        }
        __syncwarp();
    }
    int wo_next = -1;

    uint32_t ow[6];
    const int orow = wq4 * 16 + g;
    const int ok0 = 18 * wg + 2 * t;
    const uint32_t oa1 = (ok0 >> 3) * 1024 + orow * 16 + (ok0 & 7) * 2;
    const uint32_t oa0 = ((18 * wg + 16) >> 3) * 1024 + orow * 16 + ((18 * wg + 16) & 7) * 2;
#pragma unroll 1
    for (int rnd = 0; rnd < 2; rnd++) {
        uint32_t q[8];
        {
            const uint8_t* qs = smem + SM_A + orow * 304 + (4 * rnd + wg) * 36;
            q[0] = *(const uint32_t*)(qs + 4 * t); q[1] = *(const uint32_t*)(qs + 8 * 304 + 4 * t);
            q[2] = *(const uint32_t*)(qs + 16 + 4 * t); q[3] = *(const uint32_t*)(qs + 8 * 304 + 16 + 4 * t);
            q[4] = *(const uint32_t*)(qs + 32); q[5] = *(const uint32_t*)(qs + 8 * 304 + 32);
            q[6] = *(volatile uint32_t*)(misc + MI_KP + 40); q[7] = *(volatile uint32_t*)(misc + MI_KP + 40);
        }
        if (t != 0) { q[4] = 0; q[5] = 0; }
        float n0 = sq_h2(q[0]) + sq_h2(q[2]) + sq_h2(q[4]), n1 = sq_h2(q[1]) + sq_h2(q[3]) + sq_h2(q[5]);
        if (t == 1) { q[4] = 0x1800u; q[5] = 0x1800u; }
        if (rnd == 1) { __syncwarp(); if (lane == 0) mbar_arrive(BAR(B_QRD)); }
        n0 += __shfl_xor_sync(~0u, n0, 1); n1 += __shfl_xor_sync(~0u, n1, 1);
        n0 += __shfl_xor_sync(~0u, n0, 2); n1 += __shfl_xor_sync(~0u, n1, 2);
        const float qn = __uint_as_float(__reduce_max_sync(~0u, max(__float_as_uint(n0), __float_as_uint(n1)))) * 262144.0f;
        const float* kpp = (const float*)(misc + MI_KP);
        uint32_t chk = __ballot_sync(~0u, !(qn * kpp[lane & 7] <= 222.0f));
        const float ka = kpp[8], vmx = kpp[9];
        bool bad = !(qn * ka <= 4096.0f && qn <= 4096.0f && ka <= 4096.0f && vmx <= 500.0f && vmx >= 0.015625f);
        uint32_t cz = POLY_CZ + q[6], ca = POLY_CA + q[6], accor = 0;
        chk = (chk & 0xFF) | (rnd == 0 ? (warp == 4 ? 0x0C00u : (warp == 8 ? 0x8000u : 0u)) : (warp == 12 ? 0x1FE00u : 0xFE00u));

        float o[12];
#pragma unroll
        for (int i = 0; i < 12; i++) { o[i] = 0.f; asm volatile("" : "+f"(o[i]) :: "memory"); }
        uint64_t dk = mkdesc(sb, 128, 640, 0), dv = mkdesc(sb + 256, 640, 128, 0);
#pragma unroll 1
        for (int j = 0; j < 8; j++) {
            uint32_t s[64];
            if (chk & 0x100) wo_next = side_job(P, rnd, j - 1, wo_next);
            if (rnd == 0) mbar_wait(BAR(B_KVF + j));
            WG_FENCE();
            wgz_rs_n256_f16_f16(s, q[0], q[1], q[2], q[3], dk);
            wg_rs_n256_f16_f16(s, q[4], q[5], q[6], q[7], dk + 16);
            WG_COMMIT();
            if (chk & 1) {
                WG_WAIT(0);
#pragma unroll
                for (int i = 0; i < 64; i++) asm volatile("" : "+r"(s[i]) :: "memory");
#pragma unroll
                for (int i = 0; i < 64; i += 2) if ((i >> 1) & 3) accor |= s[i] | s[i + 1];
            }
            WG_WAIT(0);
#pragma unroll
            for (int i = 0; i < 64; i++) asm volatile("" : "+r"(s[i]) :: "memory");
#pragma unroll
            for (int i = 0; i < 64; i++) s[i] = ((i >> 1) & 3) ? ex2_poly(s[i], cz, ca) : ex2_mufu(s[i]);
#pragma unroll
            for (int i = 0; i < 64; i++) asm volatile("" : "+r"(s[i]) :: "memory");
            WG_FENCE();
#pragma unroll
            for (int c = 0; c < 16; c++) wg_rs_n24_f32_f16(o, s[4*c], s[4*c+1], s[4*c+2], s[4*c+3], dv + c * 80);
            WG_COMMIT();
            WG_WAIT(0);
            chk >>= 1;
            dk += 1280; dv += 1280;
        }
        if (chk & 0x100) wo_next = side_job(P, rnd, 7, wo_next);
#pragma unroll
        for (int i = 0; i < 12; i++) asm volatile("" : "+f"(o[i]) :: "memory");
        if (wq4 == 0) TS(14 + 4 * rnd + wg);
        const float l0 = __shfl_sync(~0u, o[1], (lane & 28) | 1), l1 = __shfl_sync(~0u, o[3], (lane & 28) | 1);
        bad = bad || (accor & 0xF800F800u) || !(l0 >= 64.0f && l0 <= 1e30f && l1 >= 64.0f && l1 <= 1e30f);
        const float i0 = frcp(l0), i1 = frcp(l1);
        ow[0] = pk_bf(o[0] * i0, o[1] * i0); ow[1] = pk_bf(o[2] * i1, o[3] * i1);
        ow[2] = pk_bf(o[4] * i0, o[5] * i0); ow[3] = pk_bf(o[6] * i1, o[7] * i1);
        ow[4] = pk_bf(o[8] * i0, o[9] * i0); ow[5] = pk_bf(o[10] * i1, o[11] * i1);
        if (__any_sync(~0u, bad)) {
            uint32_t res[6];
            attn_safe(P.x, P.wq, qb * 64 + wq4 * 16, hg * 8 + 4 * rnd + wg, res);
#pragma unroll
            for (int i = 0; i < 6; i++) ow[i] = res[i];
        }
#pragma unroll
        for (int i = 0; i < 6; i++) ow[i] = nz(ow[i]);
        mbar_wait(BAR(B_ZOK));
        uint8_t* go = (uint8_t*)g_ll.o[qb][4 * rnd + hg];
        st_rlx4(go + oa1, ow[2]); st_rlx4(go + oa1 + 128, ow[3]);
        st_rlx4(go + oa1 + 1024, ow[4]); st_rlx4(go + oa1 + 1152, ow[5]);
        if (t == 3) { st_rlx4(go + oa0, ow[0]); st_rlx4(go + oa0 + 128, ow[1]); }
        if (rnd == 0) {
            uint8_t* so = smem + SM_OHI;
            *(uint32_t*)(so + oa1) = ow[2]; *(uint32_t*)(so + oa1 + 128) = ow[3];
            *(uint32_t*)(so + oa1 + 1024) = ow[4]; *(uint32_t*)(so + oa1 + 1152) = ow[5];
            if (t == 3) { *(uint32_t*)(so + oa0) = ow[0]; *(uint32_t*)(so + oa0 + 128) = ow[1]; }
            PROXY_FENCE_SMEM();
            __syncwarp();
            if (lane == 0) mbar_arrive(BAR(B_OHI));
        }
    }

    uint32_t hw[36];
    float2 st0, st1;
    uint32_t key0 = 0, key1 = 0;
    if (wg == 0) {
        float acc[72];
        mbar_wait(BAR(B_WO0));
        mbar_wait(BAR(B_OHI));
        WG_FENCE();
#pragma unroll
        for (int s = 0; s < 18; s++) {
            const uint64_t da = mkdesc(sb + SM_OHI + s * 2048, 1024, 128, 0), db = mkdesc(sb + s * 4608, 2304, 128, 0);
            if (s == 0) wgz_ss_n144_f32_bf16(acc, da, db); else wg_ss_n144_f32_bf16(acc, da, db);
            if (s == 10) WG_COMMIT();
        }
        WG_COMMIT();
        BAR_SYNC(6, 512);
        {
            uint8_t* so = smem + SM_OLO;
            *(uint32_t*)(so + oa1) = ow[2]; *(uint32_t*)(so + oa1 + 128) = ow[3];
            *(uint32_t*)(so + oa1 + 1024) = ow[4]; *(uint32_t*)(so + oa1 + 1152) = ow[5];
            if (t == 3) { *(uint32_t*)(so + oa0) = ow[0]; *(uint32_t*)(so + oa0 + 128) = ow[1]; }
            PROXY_FENCE_SMEM();
        }
        WG_WAIT(1);
        if (lane == 0) mbar_arrive(BAR(B_OC));
        BAR_SYNC(7, 512);
        TS(22);
        WG_FENCE();
#pragma unroll
        for (int s = 18; s < 30; s++) {
            const uint64_t da = mkdesc(sb + SM_OLO + (s - 18) * 2048, 1024, 128, 0);
            const uint64_t db = mkdesc(sb + (s < 26 ? s * 4608 : SM_A + (s - 26) * 4608), 2304, 128, 0);
            wg_ss_n144_f32_bf16(acc, da, db);
        }
        WG_COMMIT();
        WG_WAIT(1);
        if (lane == 0) mbar_arrive(BAR(B_OM));
        mbar_wait(BAR(B_WO1));
        WG_FENCE();
#pragma unroll
        for (int s = 30; s < 36; s++) {
            const uint64_t da = mkdesc(sb + SM_OLO + (s - 18) * 2048, 1024, 128, 0), db = mkdesc(sb + (s - 30) * 4608, 2304, 128, 0);
            wg_ss_n144_f32_bf16(acc, da, db);
        }
        WG_COMMIT();
        WG_WAIT(0);
        if (lane == 0) mbar_arrive(BAR(B_OE));
#pragma unroll
        for (int i = 0; i < 72; i++) asm volatile("" : "+f"(acc[i]) :: "memory");
        TS(23);
        float sm[4] = {0, 0, 0, 0}, g1[4] = {0, 0, 0, 0}, g2[4] = {0, 0, 0, 0}, sw[4] = {0, 0, 0, 0};
        const uint32_t xaddr = sb + SM_XS + (wq4 * 16 + (lane & 15)) * 304 + (lane >> 4) * 16;
#pragma unroll
        for (int s = 0; s < 9; s++) {
            uint32_t xr[4];
            ldsm4(xr, xaddr + s * 32);
            uint32_t w0 = *(const uint32_t*)(smem + SM_XS + 64 * 304 + s * 32 + t * 4), w1 = *(const uint32_t*)(smem + SM_XS + 64 * 304 + s * 32 + 16 + t * 4);
            if (g != 1) { w0 = 0x3F803F80u; w1 = 0x3F803F80u; }
#pragma unroll
            for (int i = 0; i < 4; i++) hw[4*s+i] = nz(add_bf2(xr[i], pk_bf(acc[8*s+2*i], acc[8*s+2*i+1])));
            mma_bf16(sm, hw[4*s], hw[4*s+1], hw[4*s+2], hw[4*s+3], w0, w1);
            mma_bf16(g1, hw[4*s], hw[4*s+1], hw[4*s+2], hw[4*s+3], hw[4*s], hw[4*s+2]);
            mma_bf16(g2, hw[4*s], hw[4*s+1], hw[4*s+2], hw[4*s+3], hw[4*s+1], hw[4*s+3]);
            mma_bf16(sw, 0x3F803F80u, 0x3F803F80u, 0x3F803F80u, 0x3F803F80u, w0, w1);
        }
        const int dl = (lane & 28) | (g >> 1);
        const float q0 = __shfl_sync(~0u, (g & 1) ? g1[1] : g1[0], dl), q1 = __shfl_sync(~0u, (g & 1) ? g2[3] : g2[2], dl);
        float4* part = g_ll.part[qb][hg] + orow;
        if (t == 0) {
            st_rlx16(part, nzf(sm[0]), nzf(q0), nzf(sm[1]), nzf(sw[1]));
            st_rlx16(part + 8, nzf(sm[2]), nzf(q1), nzf(sm[3]), nzf(sw[1]));
        }
        uint32_t* gh = g_ll.h[qb * 64 + orow] + hg * 72 + t;
#pragma unroll
        for (int b = 0; b < 18; b++) { st_rlx4(gh + 4 * b, hw[2*b]); st_rlx4(gh + 8 * 288 + 4 * b, hw[2*b+1]); }
        const float4* pin = g_ll.part[qb][t] + orow;
        uint4 p0 = ld_rlx16(pin), p1 = ld_rlx16(pin + 8);
        ll_fix16(p0, pin); ll_fix16(p1, pin + 8);
        float v[8] = {__uint_as_float(p0.x), __uint_as_float(p0.y), __uint_as_float(p0.z), __uint_as_float(p0.w),
                      __uint_as_float(p1.x), __uint_as_float(p1.y), __uint_as_float(p1.z), 0.f};
        __syncwarp();
#pragma unroll
        for (int i = 0; i < 7; i++) { v[i] += __shfl_xor_sync(~0u, v[i], 1); v[i] += __shfl_xor_sync(~0u, v[i], 2); }
        st0 = ln_stats(v[0], v[1]); st1 = ln_stats(v[4], v[5]);
        uint32_t u0 = __float_as_uint((v[2] - st0.x * v[3]) * st0.y), u1 = __float_as_uint((v[6] - st1.x * v[3]) * st1.y);
        u0 = (u0 & 0x80000000u) ? ~u0 : (u0 | 0x80000000u); u1 = (u1 & 0x80000000u) ? ~u1 : (u1 | 0x80000000u);
        const int row = qb * 64 + orow;
        key0 = nz((u0 & 0xFFFFF800u) | (2047 - row)); key1 = nz((u1 & 0xFFFFF800u) | (2047 - (row + 8)));
        if (wq4 == hg) {
            if (t == 0) { st_rlx4(&g_ll.rkey[row], key0); st_rlx8(&g_ll.stat2[row], nzf(st0.x), nzf(st0.y)); }
            if (t == 1) { st_rlx4(&g_ll.rkey[row + 8], key1); st_rlx8(&g_ll.stat2[row + 8], nzf(st1.x), nzf(st1.y)); }
        }
        TS(24);
    } else {
        const uint4* src = (const uint4*)g_ll.o[qb][4 + ((hg + wg) & 3)] + (tid & 127);
        uint4 v[5];
#pragma unroll
        for (int j = 0; j < 5; j++) if (j < 4 || (tid & 127) < 64) v[j] = ld_rlx16(src + j * 128);
        BAR_SYNC(6, 512);
        uint8_t* so = smem + SM_OLO;
        *(uint32_t*)(so + oa1) = ow[2]; *(uint32_t*)(so + oa1 + 128) = ow[3];
        *(uint32_t*)(so + oa1 + 1024) = ow[4]; *(uint32_t*)(so + oa1 + 1152) = ow[5];
        if (t == 3) { *(uint32_t*)(so + oa0) = ow[0]; *(uint32_t*)(so + oa0 + 128) = ow[1]; }
        uint4* dst = (uint4*)(so + wg * 9216) + (tid & 127);
#pragma unroll
        for (int j = 0; j < 5; j++) if (j < 4 || (tid & 127) < 64) { ll_fix16(v[j], src + j * 128); dst[j * 128] = v[j]; }
        PROXY_FENCE_SMEM();
        BAR_ARRIVE(7, 512);
        if (warp == 12) {
            if (lane == 0) {
                mbar_wait(BAR(B_OC));
                mbar_expect(BAR(B_WO1), 6 * 4608 + 65 * 288);
                bulk_ld(sb, g_wo + hg * 10368 + 30 * 288, 6 * 4608, BAR(B_WO1));
                bulk_ld(sb + SM_XS + 64 * 304, P.wr + hg * 144, 288, BAR(B_WO1));
            }
            __syncwarp();
            for (int r = lane; r < 64; r += 32) bulk_ld(sb + SM_XS + r * 304, P.x + (qb * 64 + r) * DM + hg * 144, 288, BAR(B_WO1));
        } else if (warp == 13) {
            const int fc0 = (cta * 36) & ~7;
            if (lane == 0) {
                mbar_wait(BAR(B_OM));
                mbar_expect(BAR(B_GU), 4 * 15360);
                tma2d(sb + SM_G0, &tm_g, fc0, 0, BAR(B_GU));
                tma2d(sb + SM_U0, &tm_u, fc0, 0, BAR(B_GU));
                tma2d(sb + SM_G1, &tm_g, fc0, 192, BAR(B_GU));
                tma2d(sb + SM_U1, &tm_u, fc0, 192, BAR(B_GU));
                mbar_wait(BAR(B_OE));
                mbar_expect(BAR(B_GU), 2 * 15360);
                tma2d(sb + SM_G2, &tm_g, fc0, 384, BAR(B_GU));
                tma2d(sb + SM_U2, &tm_u, fc0, 384, BAR(B_GU));
                mbar_expect(BAR(B_DN), 36 * 1152);
            }
            __syncwarp();
            for (int r = lane; r < 36; r += 32) bulk_ld(sb + SM_DN + r * 1168, P.wd + (cta * 36 + r) * DM, 1152, BAR(B_DN));
        }
        mbar_wait(BAR(B_OE));
    }

    uint32_t mykey, key8;
    {
        const uint4* src = (const uint4*)g_ll.rkey + tid;
        uint4 k = ld_rlx16(src);
        ll_fix16(k, src);
        __syncwarp();
        const uint32_t wm = __reduce_max_sync(~0u, max(max(k.x, k.y), max(k.z, k.w)));
        uint32_t* wmax = (uint32_t*)(misc + MI_WMAX);
        if (lane == 0) wmax[warp] = wm;
        BAR_SYNC(8, 512);
        if (warp == 0) TS(25);
        const uint32_t mv = wmax[lane & 15];
        int cnt = 0;
#pragma unroll
        for (int j = 0; j < 4; j++) { const uint4 u = ((const uint4*)wmax)[j]; cnt += (u.x > mv) + (u.y > mv) + (u.z > mv) + (u.w > mv); }
        const uint32_t T = __reduce_max_sync(~0u, cnt >= 7 ? mv : 0u);
        uint32_t* cand = (uint32_t*)(misc + MI_RED);
        uint32_t* nc = (uint32_t*)(misc + MI_NC);
        if (k.x >= T) cand[atomicAdd(nc, 1)] = k.x;
        if (k.y >= T) cand[atomicAdd(nc, 1)] = k.y;
        if (k.z >= T) cand[atomicAdd(nc, 1)] = k.z;
        if (k.w >= T) cand[atomicAdd(nc, 1)] = k.w;
        BAR_SYNC(8, 512);
        const int n = *nc;
        uint32_t a = 0, b = 0;
#pragma unroll 1
        for (int i = lane; i < n; i += 32) {
            const uint32_t c = cand[i];
            int r = 0;
#pragma unroll 4
            for (int j = 0; j < n; j++) r += cand[j] > c;
            if (r == (warp >> 1)) a = c;
            if (r == 7) b = c;
        }
        __syncwarp();
        mykey = __reduce_max_sync(~0u, a); key8 = __reduce_max_sync(~0u, b);
    }
    {
        const int tok = 2047 - (mykey & 2047), tk = warp >> 1, p = (warp & 1) * 36 + lane;
        const uint4* src = (const uint4*)g_ll.h[tok] + p;
        uint4 a = ld_rlx16(src), b;
        if (lane < 4) b = ld_rlx16(src + 32);
        uint2 su = ld_rlx8(&g_ll.stat2[tok]);
        ll_fix8(su, &g_ll.stat2[tok]);
        const float inv = __uint_as_float(su.y);
        const uint32_t m2 = (su.x >> 16) * 0x10001u;
        ll_fix16(a, src);
        *(uint4*)(smem + SM_HS + tk * 1168 + p * 16) = a;
        *(uint4*)(smem + SM_HN + tk * 1168 + p * 16) = make_uint4(ln_apply(a.x, m2, inv), ln_apply(a.y, m2, inv), ln_apply(a.z, m2, inv), ln_apply(a.w, m2, inv));
        if (lane < 4) {
            ll_fix16(b, src + 32);
            *(uint4*)(smem + SM_HS + tk * 1168 + (p + 32) * 16) = b;
            *(uint4*)(smem + SM_HN + tk * 1168 + (p + 32) * 16) = make_uint4(ln_apply(b.x, m2, inv), ln_apply(b.y, m2, inv), ln_apply(b.z, m2, inv), ln_apply(b.w, m2, inv));
        }
        if (lane == 0 && (warp & 1) == 0) {
            uint32_t u = (mykey & 0xFFFFF800u) | 0x400u;
            u = (u & 0x80000000u) ? (u & 0x7FFFFFFFu) : ~u;
            const float r = bfr(__uint_as_float(u));
            ((float2*)(misc + MI_SEL))[tk] = make_float2(__int_as_float(tok), bfr(frcp(1.0f + __expf(-r))));
        }
    }
    BAR_SYNC(8, 512);
    if (warp == 0) TS(26);

    mbar_wait(BAR(B_GU));
    if (warp == 0) TS(27);
    if (warp < 15) {
        const int mt = warp % 5, kt = warp / 5, mat = lane >> 3, r = lane & 7;
        const uint32_t gb = kt == 0 ? SM_G0 : (kt == 1 ? SM_G1 : SM_G2);
        const uint32_t wa = sb + gb + (mat & 1) * 15360 + ((mat >> 1) * 8 + r) * 80 + mt * 16;
        const uint32_t ha = sb + SM_HN + r * 1168 + (kt * 192 + 8 * mat) * 2;
        float c0[4] = {0, 0, 0, 0}, c1[4] = {0, 0, 0, 0};
#pragma unroll
        for (int s = 0; s < 6; s++) {
            uint32_t a0[4], a1[4], b[4];
            ldsm4t(a0, wa + s * 2560); ldsm4t(a1, wa + s * 2560 + 1280); ldsm4(b, ha + s * 64);
            mma_bf16(c0, a0[0], a0[1], a0[2], a0[3], b[0], b[1]);
            mma_bf16(c1, a1[0], a1[1], a1[2], a1[3], b[2], b[3]);
        }
        ((float4*)(misc + MI_RED))[warp * 32 + lane] = make_float4(c0[0] + c1[0], c0[1] + c1[1], c0[2] + c1[2], c0[3] + c1[3]);
    }
    BAR_SYNC(8, 512);
    if (warp < 5) {
        const float4* red = (const float4*)(misc + MI_RED) + tid;
        const float4 a = red[0], b = red[160], c = red[320];
        const float g0 = bfr(a.x + b.x + c.x), g1 = bfr(a.y + b.y + c.y), u0 = bfr(a.z + b.z + c.z), u1 = bfr(a.w + b.w + c.w);
        const float y0 = bfr(g0 * frcp(1.0f + __expf(-g0))) * u0, y1 = bfr(g1 * frcp(1.0f + __expf(-g1))) * u1;
        const int f = 8 * warp + g - (cta & 1) * 4;
        if (f >= 0 && f < 36) {
            bf16* act = (bf16*)(misc + MI_ACT);
            act[(2 * t) * 56 + f] = __float2bfloat16_rn(y0);
            act[(2 * t + 1) * 56 + f] = __float2bfloat16_rn(y1);
        }
    }
    BAR_SYNC(8, 512);
    mbar_wait(BAR(B_DN));
    if (warp == 0) TS(28);
    {
        uint32_t b[6];
#pragma unroll
        for (int i = 0; i < 6; i++) b[i] = *(const uint32_t*)(misc + MI_ACT + g * 112 + i * 16 + t * 4);
        const int mat = lane >> 3, r = lane & 7;
#pragma unroll
        for (int it = 0; it < 3; it++) {
            const int mt = warp + 16 * it;
            if (mt < 36) {
                float c[4] = {0, 0, 0, 0};
#pragma unroll
                for (int s = 0; s < 3; s++) {
                    uint32_t a[4];
                    ldsm4t(a, sb + SM_DN + min(16 * s + (mat >> 1) * 8 + r, 35) * 1168 + (16 * mt + (mat & 1) * 8) * 2);
                    mma_bf16(c, a[0], a[1], a[2], a[3], b[2*s], b[2*s+1]);
                }
                st_rlx8(&g_ll.y[2 * mt][cta][2 * lane], nzf(c[0]), nzf(c[1]));
                st_rlx8(&g_ll.y[2 * mt + 1][cta][2 * lane], nzf(c[2]), nzf(c[3]));
            }
        }
    }
    if (warp == 0) TS(29);
    if (wg == 0) {
        const uint32_t m0 = (__float_as_uint(st0.x) >> 16) * 0x10001u, m1 = (__float_as_uint(st1.x) >> 16) * 0x10001u;
        uint32_t* po = (uint32_t*)(P.out + (qb * 64 + orow) * DM + hg * 144) + t;
#pragma unroll
        for (int b = 0; b < 18; b++) {
            if (key0 < key8) po[4 * b] = add_bf2(hw[2*b], ln_apply(hw[2*b], m0, st0.y));
            if (key1 < key8) po[8 * 288 + 4 * b] = add_bf2(hw[2*b+1], ln_apply(hw[2*b+1], m1, st1.y));
        }
    }
    if (cta < 72) {
        const uint4* src = (const uint4*)g_ll.y[cta] + tid;
        uint4 v[4];
#pragma unroll
        for (int j = 0; j < 4; j++) v[j] = ld_rlx16(src + j * 512);
        float4 s = make_float4(0, 0, 0, 0);
#pragma unroll
        for (int j = 0; j < 4; j++) {
            ll_fix16(v[j], src + j * 512);
            s.x += __uint_as_float(v[j].x); s.y += __uint_as_float(v[j].y); s.z += __uint_as_float(v[j].z); s.w += __uint_as_float(v[j].w);
        }
        __syncwarp();
        s.x += __shfl_xor_sync(~0u, s.x, 16); s.y += __shfl_xor_sync(~0u, s.y, 16);
        s.z += __shfl_xor_sync(~0u, s.z, 16); s.w += __shfl_xor_sync(~0u, s.w, 16);
        if (lane < 16) ((float4*)(misc + MI_RED))[warp * 16 + lane] = s;
        BAR_SYNC(8, 512);
        if (warp == 0) TS(30);
        if (tid < 64) {
            float y = 0.f;
#pragma unroll
            for (int w = 0; w < 16; w++) y += ((const float*)(misc + MI_RED))[w * 64 + tid];
            const int tk = tid & 7, col = cta * 8 + (tid >> 3);
            const float2 sel = ((const float2*)(misc + MI_SEL))[tk];
            const float hn = __bfloat162float(((const bf16*)(smem + SM_HN + tk * 1168))[col]);
            const float h = __bfloat162float(((const bf16*)(smem + SM_HS + tk * 1168))[col]);
            P.out[__float_as_int(sel.x) * DM + col] = __float2bfloat16_rn(h + bfr(hn + bfr(bfr(y) * sel.y)));
        }
        if (cta == 0 && tid == 0) { g_cnt[0] = 0; g_cnt[32] = 0; }
    }
    if (warp == 0) TS(31);
}

typedef CUresult (*EncodeFn)(CUtensorMap*, CUtensorMapDataType, cuuint32_t, void*, const cuuint64_t*, const cuuint64_t*,
                             const cuuint32_t*, const cuuint32_t*, CUtensorMapInterleave, CUtensorMapSwizzle,
                             CUtensorMapL2promotion, CUtensorMapFloatOOBfill);

static void make_map(EncodeFn enc, CUtensorMap* tm, const void* p, int cols, int rows, int bc, int br, CUtensorMapSwizzle sw) {
    cuuint64_t gd[2] = {(cuuint64_t)cols, (cuuint64_t)rows}, gs[1] = {(cuuint64_t)cols * 2};
    cuuint32_t bx[2] = {(cuuint32_t)bc, (cuuint32_t)br}, es[2] = {1, 1};
    enc(tm, CU_TENSOR_MAP_DATA_TYPE_BFLOAT16, 2, (void*)p, gd, gs, bx, es, CU_TENSOR_MAP_INTERLEAVE_NONE, sw,
        CU_TENSOR_MAP_L2_PROMOTION_L2_128B, CU_TENSOR_MAP_FLOAT_OOB_FILL_NONE);
}

extern "C" void kernel_launch(void* const* d_in, const int* in_sizes, int n_in, void* d_out, int out_size) {
    static EncodeFn enc = nullptr;
    if (!enc) {
        void* fn = nullptr;
        cudaDriverEntryPointQueryResult qr;
        cudaGetDriverEntryPoint("cuTensorMapEncodeTiled", &fn, cudaEnableDefault, &qr);
        enc = (EncodeFn)fn;
        cudaFuncSetAttribute(fused_block, cudaFuncAttributeMaxDynamicSharedMemorySize, SM_TOTAL);
    }
    Params P;
    P.x = (const bf16*)d_in[0]; P.wq = (const bf16*)d_in[1]; P.wk = (const bf16*)d_in[2]; P.wv = (const bf16*)d_in[3];
    P.wo = (const bf16*)d_in[4]; P.wr = (const bf16*)d_in[6]; P.wg = (const bf16*)d_in[7]; P.wu = (const bf16*)d_in[8];
    P.wd = (const bf16*)d_in[9]; P.out = (bf16*)d_out;
    CUtensorMap tx, twq, twqt, tg, tu;
    make_map(enc, &tx, P.x, DM, SEQ, 64, 64, CU_TENSOR_MAP_SWIZZLE_128B);
    make_map(enc, &twq, P.wq, DM, DM, 64, 64, CU_TENSOR_MAP_SWIZZLE_128B);
    make_map(enc, &twqt, P.wq, DM, DM, 16, 64, CU_TENSOR_MAP_SWIZZLE_32B);
    make_map(enc, &tg, P.wg, FF, DM, 40, 192, CU_TENSOR_MAP_SWIZZLE_NONE);
    make_map(enc, &tu, P.wu, FF, DM, 40, 192, CU_TENSOR_MAP_SWIZZLE_NONE);
    fused_block<<<NCTA, NTHR, SM_TOTAL, cudaStreamPerThread>>>(tx, twq, twqt, tg, tu, P);
}
```

```cpp
#include <cuda_runtime.h>
#include <cuda_bf16.h>
#include <cuda_fp16.h>
#include <cuda.h>
#include <stdint.h>

#define POLY_DEG3 0

__device__ __forceinline__ void wgz_rs_n256_f16_f16(uint32_t* d, uint32_t a0, uint32_t a1, uint32_t a2, uint32_t a3, uint64_t db) {
  asm volatile("{\n.reg .pred p;\nsetp.ne.b32 p, 0, 0;\n"
    "wgmma.mma_async.sync.aligned.m64n256k16.f16.f16.f16 "
    "{%0,%1,%2,%3,%4,%5,%6,%7,%8,%9,%10,%11,%12,%13,%14,%15,%16,%17,%18,%19,%20,%21,%22,%23,%24,%25,%26,%27,%28,%29,%30,%31,%32,%33,%34,%35,%36,%37,%38,%39,%40,%41,%42,%43,%44,%45,%46,%47,%48,%49,%50,%51,%52,%53,%54,%55,%56,%57,%58,%59,%60,%61,%62,%63}, "
    "{%64,%65,%66,%67}, %68, p, 1, 1, 0;\n}\n"
    : "=r"(d[0]), "=r"(d[1]), "=r"(d[2]), "=r"(d[3]), "=r"(d[4]), "=r"(d[5]), "=r"(d[6]), "=r"(d[7]),
      "=r"(d[8]), "=r"(d[9]), "=r"(d[10]), "=r"(d[11]), "=r"(d[12]), "=r"(d[13]), "=r"(d[14]), "=r"(d[15]),
      "=r"(d[16]), "=r"(d[17]), "=r"(d[18]), "=r"(d[19]), "=r"(d[20]), "=r"(d[21]), "=r"(d[22]), "=r"(d[23]),
      "=r"(d[24]), "=r"(d[25]), "=r"(d[26]), "=r"(d[27]), "=r"(d[28]), "=r"(d[29]), "=r"(d[30]), "=r"(d[31]),
      "=r"(d[32]), "=r"(d[33]), "=r"(d[34]), "=r"(d[35]), "=r"(d[36]), "=r"(d[37]), "=r"(d[38]), "=r"(d[39]),
      "=r"(d[40]), "=r"(d[41]), "=r"(d[42]), "=r"(d[43]), "=r"(d[44]), "=r"(d[45]), "=r"(d[46]), "=r"(d[47]),
      "=r"(d[48]), "=r"(d[49]), "=r"(d[50]), "=r"(d[51]), "=r"(d[52]), "=r"(d[53]), "=r"(d[54]), "=r"(d[55]),
      "=r"(d[56]), "=r"(d[57]), "=r"(d[58]), "=r"(d[59]), "=r"(d[60]), "=r"(d[61]), "=r"(d[62]), "=r"(d[63])
    : "r"(a0), "r"(a1), "r"(a2), "r"(a3), "l"(db));
}
__device__ __forceinline__ void wg_rs_n256_f16_f16(uint32_t* d, uint32_t a0, uint32_t a1, uint32_t a2, uint32_t a3, uint64_t db) {
  asm volatile("{\n.reg .pred p;\nsetp.ne.b32 p, 1, 0;\n"
    "wgmma.mma_async.sync.aligned.m64n256k16.f16.f16.f16 "
    "{%0,%1,%2,%3,%4,%5,%6,%7,%8,%9,%10,%11,%12,%13,%14,%15,%16,%17,%18,%19,%20,%21,%22,%23,%24,%25,%26,%27,%28,%29,%30,%31,%32,%33,%34,%35,%36,%37,%38,%39,%40,%41,%42,%43,%44,%45,%46,%47,%48,%49,%50,%51,%52,%53,%54,%55,%56,%57,%58,%59,%60,%61,%62,%63}, "
    "{%64,%65,%66,%67}, %68, p, 1, 1, 0;\n}\n"
    : "+r"(d[0]), "+r"(d[1]), "+r"(d[2]), "+r"(d[3]), "+r"(d[4]), "+r"(d[5]), "+r"(d[6]), "+r"(d[7]),
      "+r"(d[8]), "+r"(d[9]), "+r"(d[10]), "+r"(d[11]), "+r"(d[12]), "+r"(d[13]), "+r"(d[14]), "+r"(d[15]),
      "+r"(d[16]), "+r"(d[17]), "+r"(d[18]), "+r"(d[19]), "+r"(d[20]), "+r"(d[21]), "+r"(d[22]), "+r"(d[23]),
      "+r"(d[24]), "+r"(d[25]), "+r"(d[26]), "+r"(d[27]), "+r"(d[28]), "+r"(d[29]), "+r"(d[30]), "+r"(d[31]),
      "+r"(d[32]), "+r"(d[33]), "+r"(d[34]), "+r"(d[35]), "+r"(d[36]), "+r"(d[37]), "+r"(d[38]), "+r"(d[39]),
      "+r"(d[40]), "+r"(d[41]), "+r"(d[42]), "+r"(d[43]), "+r"(d[44]), "+r"(d[45]), "+r"(d[46]), "+r"(d[47]),
      "+r"(d[48]), "+r"(d[49]), "+r"(d[50]), "+r"(d[51]), "+r"(d[52]), "+r"(d[53]), "+r"(d[54]), "+r"(d[55]),
      "+r"(d[56]), "+r"(d[57]), "+r"(d[58]), "+r"(d[59]), "+r"(d[60]), "+r"(d[61]), "+r"(d[62]), "+r"(d[63])
    : "r"(a0), "r"(a1), "r"(a2), "r"(a3), "l"(db));
}
__device__ __forceinline__ void wg_rs_n24_f32_f16(float* d, uint32_t a0, uint32_t a1, uint32_t a2, uint32_t a3, uint64_t db) {
  asm volatile("{\n.reg .pred p;\nsetp.ne.b32 p, 1, 0;\n"
    "wgmma.mma_async.sync.aligned.m64n24k16.f32.f16.f16 "
    "{%0,%1,%2,%3,%4,%5,%6,%7,%8,%9,%10,%11}, "
    "{%12,%13,%14,%15}, %16, p, 1, 1, 1;\n}\n"
    : "+f"(d[0]), "+f"(d[1]), "+f"(d[2]), "+f"(d[3]), "+f"(d[4]), "+f"(d[5]), "+f"(d[6]), "+f"(d[7]),
      "+f"(d[8]), "+f"(d[9]), "+f"(d[10]), "+f"(d[11])
    : "r"(a0), "r"(a1), "r"(a2), "r"(a3), "l"(db));
}
__device__ __forceinline__ void wgp_rs_n24_f32_f16(float* d, uint32_t a0, uint32_t a1, uint32_t a2, uint32_t a3, uint64_t db, uint32_t sd) {
  asm volatile("{\n.reg .pred p;\nsetp.ne.b32 p, %17, 0;\n"
    "wgmma.mma_async.sync.aligned.m64n24k16.f32.f16.f16 "
    "{%0,%1,%2,%3,%4,%5,%6,%7,%8,%9,%10,%11}, "
    "{%12,%13,%14,%15}, %16, p, 1, 1, 1;\n}\n"
    : "+f"(d[0]), "+f"(d[1]), "+f"(d[2]), "+f"(d[3]), "+f"(d[4]), "+f"(d[5]), "+f"(d[6]), "+f"(d[7]),
      "+f"(d[8]), "+f"(d[9]), "+f"(d[10]), "+f"(d[11])
    : "r"(a0), "r"(a1), "r"(a2), "r"(a3), "l"(db), "r"(sd));
}
__device__ __forceinline__ void wgp_ss_n128_f32_bf16(float* d, uint64_t da, uint64_t db, uint32_t sd) {
  asm volatile("{\n.reg .pred p;\nsetp.ne.b32 p, %66, 0;\n"
    "wgmma.mma_async.sync.aligned.m64n128k16.f32.bf16.bf16 "
    "{%0,%1,%2,%3,%4,%5,%6,%7,%8,%9,%10,%11,%12,%13,%14,%15,%16,%17,%18,%19,%20,%21,%22,%23,%24,%25,%26,%27,%28,%29,%30,%31,%32,%33,%34,%35,%36,%37,%38,%39,%40,%41,%42,%43,%44,%45,%46,%47,%48,%49,%50,%51,%52,%53,%54,%55,%56,%57,%58,%59,%60,%61,%62,%63}, "
    "%64, %65, p, 1, 1, 0, 1;\n}\n"
    : "+f"(d[0]), "+f"(d[1]), "+f"(d[2]), "+f"(d[3]), "+f"(d[4]), "+f"(d[5]), "+f"(d[6]), "+f"(d[7]),
      "+f"(d[8]), "+f"(d[9]), "+f"(d[10]), "+f"(d[11]), "+f"(d[12]), "+f"(d[13]), "+f"(d[14]), "+f"(d[15]),
      "+f"(d[16]), "+f"(d[17]), "+f"(d[18]), "+f"(d[19]), "+f"(d[20]), "+f"(d[21]), "+f"(d[22]), "+f"(d[23]),
      "+f"(d[24]), "+f"(d[25]), "+f"(d[26]), "+f"(d[27]), "+f"(d[28]), "+f"(d[29]), "+f"(d[30]), "+f"(d[31]),
      "+f"(d[32]), "+f"(d[33]), "+f"(d[34]), "+f"(d[35]), "+f"(d[36]), "+f"(d[37]), "+f"(d[38]), "+f"(d[39]),
      "+f"(d[40]), "+f"(d[41]), "+f"(d[42]), "+f"(d[43]), "+f"(d[44]), "+f"(d[45]), "+f"(d[46]), "+f"(d[47]),
      "+f"(d[48]), "+f"(d[49]), "+f"(d[50]), "+f"(d[51]), "+f"(d[52]), "+f"(d[53]), "+f"(d[54]), "+f"(d[55]),
      "+f"(d[56]), "+f"(d[57]), "+f"(d[58]), "+f"(d[59]), "+f"(d[60]), "+f"(d[61]), "+f"(d[62]), "+f"(d[63])
    : "l"(da), "l"(db), "r"(sd));
}
__device__ __forceinline__ void wg_ss_n128_f32_bf16(float* d, uint64_t da, uint64_t db) {
  asm volatile("{\n.reg .pred p;\nsetp.ne.b32 p, 1, 0;\n"
    "wgmma.mma_async.sync.aligned.m64n128k16.f32.bf16.bf16 "
    "{%0,%1,%2,%3,%4,%5,%6,%7,%8,%9,%10,%11,%12,%13,%14,%15,%16,%17,%18,%19,%20,%21,%22,%23,%24,%25,%26,%27,%28,%29,%30,%31,%32,%33,%34,%35,%36,%37,%38,%39,%40,%41,%42,%43,%44,%45,%46,%47,%48,%49,%50,%51,%52,%53,%54,%55,%56,%57,%58,%59,%60,%61,%62,%63}, "
    "%64, %65, p, 1, 1, 0, 1;\n}\n"
    : "+f"(d[0]), "+f"(d[1]), "+f"(d[2]), "+f"(d[3]), "+f"(d[4]), "+f"(d[5]), "+f"(d[6]), "+f"(d[7]),
      "+f"(d[8]), "+f"(d[9]), "+f"(d[10]), "+f"(d[11]), "+f"(d[12]), "+f"(d[13]), "+f"(d[14]), "+f"(d[15]),
      "+f"(d[16]), "+f"(d[17]), "+f"(d[18]), "+f"(d[19]), "+f"(d[20]), "+f"(d[21]), "+f"(d[22]), "+f"(d[23]),
      "+f"(d[24]), "+f"(d[25]), "+f"(d[26]), "+f"(d[27]), "+f"(d[28]), "+f"(d[29]), "+f"(d[30]), "+f"(d[31]),
      "+f"(d[32]), "+f"(d[33]), "+f"(d[34]), "+f"(d[35]), "+f"(d[36]), "+f"(d[37]), "+f"(d[38]), "+f"(d[39]),
      "+f"(d[40]), "+f"(d[41]), "+f"(d[42]), "+f"(d[43]), "+f"(d[44]), "+f"(d[45]), "+f"(d[46]), "+f"(d[47]),
      "+f"(d[48]), "+f"(d[49]), "+f"(d[50]), "+f"(d[51]), "+f"(d[52]), "+f"(d[53]), "+f"(d[54]), "+f"(d[55]),
      "+f"(d[56]), "+f"(d[57]), "+f"(d[58]), "+f"(d[59]), "+f"(d[60]), "+f"(d[61]), "+f"(d[62]), "+f"(d[63])
    : "l"(da), "l"(db));
}
__device__ __forceinline__ void wgp_ss_n16_f32_bf16(float* d, uint64_t da, uint64_t db, uint32_t sd) {
  asm volatile("{\n.reg .pred p;\nsetp.ne.b32 p, %10, 0;\n"
    "wgmma.mma_async.sync.aligned.m64n16k16.f32.bf16.bf16 "
    "{%0,%1,%2,%3,%4,%5,%6,%7}, "
    "%8, %9, p, 1, 1, 0, 1;\n}\n"
    : "+f"(d[0]), "+f"(d[1]), "+f"(d[2]), "+f"(d[3]), "+f"(d[4]), "+f"(d[5]), "+f"(d[6]), "+f"(d[7])
    : "l"(da), "l"(db), "r"(sd));
}
__device__ __forceinline__ void wg_ss_n16_f32_bf16(float* d, uint64_t da, uint64_t db) {
  asm volatile("{\n.reg .pred p;\nsetp.ne.b32 p, 1, 0;\n"
    "wgmma.mma_async.sync.aligned.m64n16k16.f32.bf16.bf16 "
    "{%0,%1,%2,%3,%4,%5,%6,%7}, "
    "%8, %9, p, 1, 1, 0, 1;\n}\n"
    : "+f"(d[0]), "+f"(d[1]), "+f"(d[2]), "+f"(d[3]), "+f"(d[4]), "+f"(d[5]), "+f"(d[6]), "+f"(d[7])
    : "l"(da), "l"(db));
}
__device__ __forceinline__ void wgp_ss_n144_f32_bf16(float* d, uint64_t da, uint64_t db, uint32_t sd) {
  asm volatile("{\n.reg .pred p;\nsetp.ne.b32 p, %74, 0;\n"
    "wgmma.mma_async.sync.aligned.m64n144k16.f32.bf16.bf16 "
    "{%0,%1,%2,%3,%4,%5,%6,%7,%8,%9,%10,%11,%12,%13,%14,%15,%16,%17,%18,%19,%20,%21,%22,%23,%24,%25,%26,%27,%28,%29,%30,%31,%32,%33,%34,%35,%36,%37,%38,%39,%40,%41,%42,%43,%44,%45,%46,%47,%48,%49,%50,%51,%52,%53,%54,%55,%56,%57,%58,%59,%60,%61,%62,%63,%64,%65,%66,%67,%68,%69,%70,%71}, "
    "%72, %73, p, 1, 1, 0, 1;\n}\n"
    : "+f"(d[0]), "+f"(d[1]), "+f"(d[2]), "+f"(d[3]), "+f"(d[4]), "+f"(d[5]), "+f"(d[6]), "+f"(d[7]),
      "+f"(d[8]), "+f"(d[9]), "+f"(d[10]), "+f"(d[11]), "+f"(d[12]), "+f"(d[13]), "+f"(d[14]), "+f"(d[15]),
      "+f"(d[16]), "+f"(d[17]), "+f"(d[18]), "+f"(d[19]), "+f"(d[20]), "+f"(d[21]), "+f"(d[22]), "+f"(d[23]),
      "+f"(d[24]), "+f"(d[25]), "+f"(d[26]), "+f"(d[27]), "+f"(d[28]), "+f"(d[29]), "+f"(d[30]), "+f"(d[31]),
      "+f"(d[32]), "+f"(d[33]), "+f"(d[34]), "+f"(d[35]), "+f"(d[36]), "+f"(d[37]), "+f"(d[38]), "+f"(d[39]),
      "+f"(d[40]), "+f"(d[41]), "+f"(d[42]), "+f"(d[43]), "+f"(d[44]), "+f"(d[45]), "+f"(d[46]), "+f"(d[47]),
      "+f"(d[48]), "+f"(d[49]), "+f"(d[50]), "+f"(d[51]), "+f"(d[52]), "+f"(d[53]), "+f"(d[54]), "+f"(d[55]),
      "+f"(d[56]), "+f"(d[57]), "+f"(d[58]), "+f"(d[59]), "+f"(d[60]), "+f"(d[61]), "+f"(d[62]), "+f"(d[63]),
      "+f"(d[64]), "+f"(d[65]), "+f"(d[66]), "+f"(d[67]), "+f"(d[68]), "+f"(d[69]), "+f"(d[70]), "+f"(d[71])
    : "l"(da), "l"(db), "r"(sd));
}
__device__ __forceinline__ void wg_ss_n144_f32_bf16(float* d, uint64_t da, uint64_t db) {
  asm volatile("{\n.reg .pred p;\nsetp.ne.b32 p, 1, 0;\n"
    "wgmma.mma_async.sync.aligned.m64n144k16.f32.bf16.bf16 "
    "{%0,%1,%2,%3,%4,%5,%6,%7,%8,%9,%10,%11,%12,%13,%14,%15,%16,%17,%18,%19,%20,%21,%22,%23,%24,%25,%26,%27,%28,%29,%30,%31,%32,%33,%34,%35,%36,%37,%38,%39,%40,%41,%42,%43,%44,%45,%46,%47,%48,%49,%50,%51,%52,%53,%54,%55,%56,%57,%58,%59,%60,%61,%62,%63,%64,%65,%66,%67,%68,%69,%70,%71}, "
    "%72, %73, p, 1, 1, 0, 1;\n}\n"
    : "+f"(d[0]), "+f"(d[1]), "+f"(d[2]), "+f"(d[3]), "+f"(d[4]), "+f"(d[5]), "+f"(d[6]), "+f"(d[7]),
      "+f"(d[8]), "+f"(d[9]), "+f"(d[10]), "+f"(d[11]), "+f"(d[12]), "+f"(d[13]), "+f"(d[14]), "+f"(d[15]),
      "+f"(d[16]), "+f"(d[17]), "+f"(d[18]), "+f"(d[19]), "+f"(d[20]), "+f"(d[21]), "+f"(d[22]), "+f"(d[23]),
      "+f"(d[24]), "+f"(d[25]), "+f"(d[26]), "+f"(d[27]), "+f"(d[28]), "+f"(d[29]), "+f"(d[30]), "+f"(d[31]),
      "+f"(d[32]), "+f"(d[33]), "+f"(d[34]), "+f"(d[35]), "+f"(d[36]), "+f"(d[37]), "+f"(d[38]), "+f"(d[39]),
      "+f"(d[40]), "+f"(d[41]), "+f"(d[42]), "+f"(d[43]), "+f"(d[44]), "+f"(d[45]), "+f"(d[46]), "+f"(d[47]),
      "+f"(d[48]), "+f"(d[49]), "+f"(d[50]), "+f"(d[51]), "+f"(d[52]), "+f"(d[53]), "+f"(d[54]), "+f"(d[55]),
      "+f"(d[56]), "+f"(d[57]), "+f"(d[58]), "+f"(d[59]), "+f"(d[60]), "+f"(d[61]), "+f"(d[62]), "+f"(d[63]),
      "+f"(d[64]), "+f"(d[65]), "+f"(d[66]), "+f"(d[67]), "+f"(d[68]), "+f"(d[69]), "+f"(d[70]), "+f"(d[71])
    : "l"(da), "l"(db));
}

typedef __nv_bfloat16 bf16;
constexpr int SEQ = 2048, DM = 576, FF = 4608;
constexpr int NCTA = 128, NTHR = 512;

struct LLScratch {
    uint32_t o[NCTA][2304];
    uint32_t oflag[NCTA][8];
    uint32_t y[72][NCTA][32];
    uint32_t hn[32][8][288];
    uint32_t hs[32][8][288];
    float4   part[32][4][64];
    uint4    top[NCTA][64];
};
static_assert(sizeof(LLScratch) % (NCTA * 16) == 0, "zero slices");
struct LLFirst {
    uint4 kv[SEQ * 5];
    float2 stat1[SEQ];
    float colsum[8][4][160];
};
static_assert(sizeof(LLFirst) % (NCTA * 16) == 0, "zero slices");
struct Scratch {
    LLScratch ll;
    LLFirst l1;
    uint4 o1[NCTA][576];
    uint4 wo[4 * 36 * 288];
    float4 kvraw[SEQ * 10];
    float4 info[2 * NCTA];
    uint32_t tmp[NCTA][NTHR][8];
    uint32_t cnt[64];
};
__device__ __align__(1024) Scratch g_scratch;
constexpr uint32_t CNT1 = NCTA, CNT2 = NCTA;

#define TS(i)
#define TSG(i)
#define TSL(i)

constexpr int SM_X = 147456;
constexpr int SM_WKV = 92160;
constexpr int SM_OLO = 126976, SM_OHI = 163840;
constexpr int SM_A = 200704;
constexpr int SM_R = 92160;
constexpr int SM_XS = SM_OHI;
constexpr int SM_DN0 = SM_OHI + 20096, SM_DN1 = 0, SM_DN2 = 14464;
constexpr int SM_OUT = SM_OLO + 16384;
constexpr int SM_HN = SM_A, SM_RED = SM_A + 9344;
constexpr int SM_MISC = 221184;
constexpr int SM_BAR = SM_MISC + 10752;
constexpr int SM_TOTAL = 232448;
constexpr int MP_N2 = 2304, MP_VM = 2368, MP_ST = 2432, MP_INFO = 2560, MP_STG = 2816, MP_CS = 4096, MP_W = 5888;
constexpr int MI_STAT = 0;
constexpr int MI_CS = 512;
constexpr int MI_KP = 1088;
constexpr int MI_TOP = 1152;
constexpr int MI_ACT = 1344;
constexpr int MI_SEL = 2304;
constexpr int MI_ONE = 2560;
constexpr int MI_Z = 6400;
constexpr int SM_SW = SM_TOTAL - 16;
enum { B_KV1 = 0, B_KV2, B_C1, B_INFO, B_AUX, B_ZOK, B_OHT, B_XS, B_DN, B_GU, B_W = 10, B_WF = 19, B_KV0 = 27,
       B_G4 = 28, B_G8, B_QC = 33, B_FULL = 42, B_QRD = 52, B_KVD = 52, B_OHA = 58, B_END, B_NUM };
static_assert(B_NUM * 8 <= SM_TOTAL - SM_BAR, "barriers");

constexpr uint32_t sb = 1024;
#define BAR(i) (sb + SM_BAR + 8 * (i))

#define MARK(x)
#define MARKMASK 0
#define WG_FENCE() asm volatile("wgmma.fence.sync.aligned;" ::: "memory")
#define WG_COMMIT() asm volatile("wgmma.commit_group.sync.aligned;" ::: "memory")
#define WG_WAIT(n) asm volatile("wgmma.wait_group.sync.aligned %0;" :: "n"(n) : "memory")
#define BAR_SYNC(id, n) if ((MARKMASK >> id) & 1) MARK(__LINE__); asm volatile("barrier.cta.sync %0, %1;" :: "n"(id), "n"(n) : "memory")
#define BAR_ARRIVE(id, n) asm volatile("barrier.cta.arrive %0, %1;" :: "n"(id), "n"(n) : "memory")
#define PROXY_FENCE_GMEM() asm volatile("fence.proxy.async.global;" ::: "memory")
#define PROXY_FENCE_SMEM() asm volatile("fence.proxy.async.shared::cta;" ::: "memory")

__device__ __forceinline__ constexpr uint64_t mkdesc(uint32_t addr, uint32_t lbo, uint32_t sbo, uint32_t mode) {
    return (uint64_t)((addr & 0x3FFFF) >> 4) | ((uint64_t)(lbo >> 4) << 16) | ((uint64_t)(sbo >> 4) << 32) | ((uint64_t)mode << 62);
}
#define ELECT "{\n.reg .pred e;\nelect.sync _|e, 0xffffffff;\n@e "
__device__ __forceinline__ void mbar_init_e(uint32_t b, int c) { asm volatile(ELECT "mbarrier.init.shared::cta.b64 [%0], %1;\n}" :: "r"(b), "r"(c) : "memory"); }
__device__ __forceinline__ void mbar_expect_e(uint32_t b, uint32_t tx) { asm volatile(ELECT "mbarrier.arrive.expect_tx.shared::cta.b64 _, [%0], %1;\n}" :: "r"(b), "r"(tx) : "memory"); }
__device__ __forceinline__ void mbar_arrive_e(uint32_t b) { asm volatile(ELECT "mbarrier.arrive.shared::cta.b64 _, [%0];\n}" :: "r"(b) : "memory"); }
__device__ __forceinline__ void mbar_arrive_if(uint32_t b, bool c) {
    asm volatile("{.reg .pred p; setp.ne.u32 p, %1, 0; @p mbarrier.arrive.shared::cta.b64 _, [%0];}" :: "r"(b), "r"((uint32_t)c) : "memory");
}
__device__ __forceinline__ bool mbar_test(uint32_t b) {
    uint32_t ok;
    asm volatile("{.reg .pred p; mbarrier.test_wait.parity.shared::cta.b64 p, [%1], 0; selp.u32 %0, 1, 0, p;}" : "=r"(ok) : "r"(b) : "memory");
    return __all_sync(~0u, ok);
}
#define GIVEUP "trap;\n"
#define LIMIT "0x20000000"
#define WAITFN template <int LN> __device__ __forceinline__
#define LNDEF(n)
#define SPIN_TAIL "mov.u32 c, %%clock;\nsub.u32 c, c, c0;\nsetp.lt.u32 p, c, " LIMIT ";\n@p bra.uni W;\n" GIVEUP "D:\n}"
WAITFN void mbar_wait_(uint32_t b, uint32_t par) {
    asm volatile("{\n.reg .pred p;\n.reg .u32 c, c0;\n" LNDEF(1)
                 "mbarrier.try_wait.parity.shared::cta.b64 p, [%0], %2;\n@p bra.uni D;\nmov.u32 c0, %%clock;\n"
                 "W: .pragma \"nounroll\";\nmbarrier.try_wait.parity.shared::cta.b64 p, [%0], %2;\n@p bra.uni D;\n" SPIN_TAIL :: "r"(b), "n"(LN), "r"(par) : "memory");
}
#define mbar_wait(b) mbar_wait_<__LINE__>(b, 0)
#define mbar_wait_p(b, p) mbar_wait_<__LINE__>(b, p)
__device__ __forceinline__ void bulk_ld_e(uint32_t dst, const void* src, uint32_t bytes, uint32_t bar) {
    asm volatile(ELECT "cp.async.bulk.shared::cluster.global.mbarrier::complete_tx::bytes [%0], [%1], %2, [%3];\n}"
                 :: "r"(dst), "l"(src), "r"(bytes), "r"(bar) : "memory");
}
__device__ __forceinline__ void bulk_st_e(void* dst, uint32_t src, uint32_t bytes) {
    asm volatile(ELECT "cp.async.bulk.global.shared::cta.bulk_group [%0], [%1], %2;\n}" :: "l"(dst), "r"(src), "r"(bytes) : "memory");
}
__device__ __forceinline__ void tma2d_e(uint32_t dst, const CUtensorMap* tm, int c0, int c1, uint32_t bar) {
    asm volatile(ELECT "cp.async.bulk.tensor.2d.shared::cluster.global.mbarrier::complete_tx::bytes [%0], [%1, {%3, %4}], [%2];\n}"
                 :: "r"(dst), "l"(tm), "r"(bar), "r"(c0), "r"(c1) : "memory");
}
__device__ __forceinline__ void tma2d_st_e(const CUtensorMap* tm, int c0, int c1, uint32_t src) {
    asm volatile(ELECT "cp.async.bulk.tensor.2d.global.shared::cta.bulk_group [%0, {%2, %3}], [%1];\n}" :: "l"(tm), "r"(src), "r"(c0), "r"(c1) : "memory");
}
__device__ __forceinline__ void l2_prefetch_e(const void* src, uint32_t bytes) {
    asm volatile(ELECT "cp.async.bulk.prefetch.L2.global [%0], %1;\n}" :: "l"(src), "r"(bytes) : "memory");
}
__device__ __forceinline__ void tm_prefetch_e(const CUtensorMap* tm) { asm volatile(ELECT "prefetch.tensormap [%0];\n}" :: "l"(tm) : "memory"); }
__device__ __forceinline__ void red_release_e(uint32_t* p) { asm volatile(ELECT "red.release.gpu.global.add.u32 [%0], 1;\n}" :: "l"(p) : "memory"); }
__device__ __forceinline__ void red_relaxed_e(uint32_t* p) { asm volatile(ELECT "red.relaxed.gpu.global.add.u32 [%0], 1;\n}" :: "l"(p) : "memory"); }
WAITFN void poll_counter_(const uint32_t* p, uint32_t target) {
    asm volatile("{\n.reg .pred p;\n.reg .u32 c, c0, v;\n" LNDEF(2) "mov.u32 c0, %%clock;\n"
                 "W: .pragma \"nounroll\";\nld.acquire.gpu.global.u32 v, [%0];\nsetp.ge.u32 p, v, %1;\n@p bra.uni D;\n" SPIN_TAIL
                 :: "l"(p), "r"(target), "n"(LN) : "memory");
}
#define poll_counter(p, t) poll_counter_<__LINE__>(p, t)
__device__ __forceinline__ uint4 ld_rlx16(const void* p) {
    uint4 v;
    asm volatile("ld.relaxed.gpu.global.v4.u32 {%0,%1,%2,%3}, [%4];" : "=r"(v.x), "=r"(v.y), "=r"(v.z), "=r"(v.w) : "l"(p) : "memory");
    return v;
}
__device__ __forceinline__ uint32_t ld_rlx4(const void* p) {
    uint32_t v;
    asm volatile("ld.relaxed.gpu.global.u32 %0, [%1];" : "=r"(v) : "l"(p) : "memory");
    return v;
}
WAITFN void ll_fix16_(uint4& v, const void* p, bool act) {
    asm volatile("{\n.reg .pred p, a;\n.reg .u32 c, c0, m;\n" LNDEF(6) "setp.ne.u32 a, %5, 0;\n"
                 "min.u32 m, %0, %1;\nmin.u32 m, m, %2;\nmin.u32 m, m, %3;\nsetp.eq.and.u32 a, m, 0, a;\n"
                 "vote.sync.any.pred p, a, 0xffffffff;\n@!p bra.uni D;\nmov.u32 c0, %%clock;\n"
                 "W: .pragma \"nounroll\";\n@a ld.relaxed.gpu.global.v4.u32 {%0,%1,%2,%3}, [%4];\n"
                 "min.u32 m, %0, %1;\nmin.u32 m, m, %2;\nmin.u32 m, m, %3;\nsetp.eq.and.u32 a, m, 0, a;\n"
                 "vote.sync.any.pred p, a, 0xffffffff;\n@!p bra.uni D;\n" SPIN_TAIL
                 : "+r"(v.x), "+r"(v.y), "+r"(v.z), "+r"(v.w) : "l"(p), "r"((uint32_t)act), "n"(LN) : "memory");
}
#define ll_fix16(v, p, a) ll_fix16_<__LINE__>(v, p, a)
WAITFN void ll_fix4_(uint32_t& v, const void* p) {
    asm volatile("{\n.reg .pred p, a;\n.reg .u32 c, c0;\n" LNDEF(2) "setp.eq.u32 a, %0, 0;\n"
                 "vote.sync.any.pred p, a, 0xffffffff;\n@!p bra.uni D;\nmov.u32 c0, %%clock;\n"
                 "W: .pragma \"nounroll\";\n@a ld.relaxed.gpu.global.u32 %0, [%1];\nsetp.eq.u32 a, %0, 0;\n"
                 "vote.sync.any.pred p, a, 0xffffffff;\n@!p bra.uni D;\n" SPIN_TAIL
                 : "+r"(v) : "l"(p), "n"(LN) : "memory");
}
#define ll_fix4(v, p) ll_fix4_<__LINE__>(v, p)
__device__ __forceinline__ void st_rlx4(void* p, uint32_t a) { asm volatile("st.relaxed.gpu.global.u32 [%0], %1;" :: "l"(p), "r"(a) : "memory"); }
__device__ __forceinline__ void st_rlx8(void* p, uint32_t a, uint32_t b) { asm volatile("st.relaxed.gpu.global.v2.u32 [%0], {%1,%2};" :: "l"(p), "r"(a), "r"(b) : "memory"); }
__device__ __forceinline__ void st_rlx16(void* p, uint32_t a, uint32_t b, uint32_t c, uint32_t d) {
    asm volatile("st.relaxed.gpu.global.v4.u32 [%0], {%1,%2,%3,%4};" :: "l"(p), "r"(a), "r"(b), "r"(c), "r"(d) : "memory");
}
__device__ __forceinline__ uint32_t nz(uint32_t w) { return max(w, 1u); }
__device__ __forceinline__ uint32_t nzf(float f) { return max(__float_as_uint(f), 1u); }
__device__ __forceinline__ void mma_bf16(float* d, uint32_t a0, uint32_t a1, uint32_t a2, uint32_t a3, uint32_t b0, uint32_t b1) {
    asm volatile("mma.sync.aligned.m16n8k16.row.col.f32.bf16.bf16.f32 {%0,%1,%2,%3}, {%4,%5,%6,%7}, {%8,%9}, {%0,%1,%2,%3};"
                 : "+f"(d[0]), "+f"(d[1]), "+f"(d[2]), "+f"(d[3]) : "r"(a0), "r"(a1), "r"(a2), "r"(a3), "r"(b0), "r"(b1));
}
__device__ __forceinline__ void mma_bf16_k8(float* d, uint32_t a0, uint32_t a1, uint32_t b0) {
    asm volatile("mma.sync.aligned.m16n8k8.row.col.f32.bf16.bf16.f32 {%0,%1,%2,%3}, {%4,%5}, {%6}, {%0,%1,%2,%3};"
                 : "+f"(d[0]), "+f"(d[1]), "+f"(d[2]), "+f"(d[3]) : "r"(a0), "r"(a1), "r"(b0));
}
__device__ __forceinline__ void delay(uint32_t cyc) {
    asm volatile("{\n.reg .pred p;\n.reg .u32 c, c0;\nmov.u32 c0, %%clock;\nW: .pragma \"nounroll\";\nmov.u32 c, %%clock;\nsub.u32 c, c, c0;\n"
                 "setp.lt.u32 p, c, %0;\n@p bra.uni W;\n}" :: "r"(cyc) : "memory");
}
__device__ __forceinline__ void mma_f16(float* d, uint32_t a0, uint32_t a1, uint32_t a2, uint32_t a3, uint32_t b0, uint32_t b1) {
    asm volatile("mma.sync.aligned.m16n8k16.row.col.f32.f16.f16.f32 {%0,%1,%2,%3}, {%4,%5,%6,%7}, {%8,%9}, {%0,%1,%2,%3};"
                 : "+f"(d[0]), "+f"(d[1]), "+f"(d[2]), "+f"(d[3]) : "r"(a0), "r"(a1), "r"(a2), "r"(a3), "r"(b0), "r"(b1));
}
__device__ __forceinline__ void ldsm4(uint32_t* r, uint32_t a) {
    asm volatile("ldmatrix.sync.aligned.m8n8.x4.shared.b16 {%0,%1,%2,%3}, [%4];" : "=r"(r[0]), "=r"(r[1]), "=r"(r[2]), "=r"(r[3]) : "r"(a) : "memory");
}
__device__ __forceinline__ void ldsm4t(uint32_t* r, uint32_t a) {
    asm volatile("ldmatrix.sync.aligned.m8n8.x4.trans.shared.b16 {%0,%1,%2,%3}, [%4];" : "=r"(r[0]), "=r"(r[1]), "=r"(r[2]), "=r"(r[3]) : "r"(a) : "memory");
}
__device__ __forceinline__ void stsm4(uint32_t a, uint32_t r0, uint32_t r1, uint32_t r2, uint32_t r3) {
    asm volatile("stmatrix.sync.aligned.m8n8.x4.shared.b16 [%0], {%1,%2,%3,%4};" :: "r"(a), "r"(r0), "r"(r1), "r"(r2), "r"(r3) : "memory");
}
__device__ __forceinline__ float frcp(float x) { float r; asm("rcp.approx.ftz.f32 %0, %1;" : "=f"(r) : "f"(x)); return r; }
__device__ __forceinline__ float fsqrt(float x) { float r; asm("sqrt.approx.ftz.f32 %0, %1;" : "=f"(r) : "f"(x)); return r; }
__device__ __forceinline__ float bfr(float x) { return __bfloat162float(__float2bfloat16_rn(x)); }
__device__ __forceinline__ uint32_t pk_bf(float lo, float hi) { uint32_t r; asm("cvt.rn.bf16x2.f32 %0, %1, %2;" : "=r"(r) : "f"(hi), "f"(lo)); return r; }
__device__ __forceinline__ uint32_t pk_h(float lo, float hi) { uint32_t r; asm("cvt.rn.f16x2.f32 %0, %1, %2;" : "=r"(r) : "f"(hi), "f"(lo)); return r; }
__device__ __forceinline__ float bf_lo(uint32_t w) { return __uint_as_float(w << 16); }
__device__ __forceinline__ float bf_hi(uint32_t w) { return __uint_as_float(w & 0xFFFF0000u); }
__device__ __forceinline__ uint32_t add_bf2(uint32_t a, uint32_t b) { uint32_t r; asm("add.rn.bf16x2 %0, %1, %2;" : "=r"(r) : "r"(a), "r"(b)); return r; }
__device__ __forceinline__ uint32_t sub_bf2(uint32_t a, uint32_t b) { uint32_t r; asm("sub.rn.bf16x2 %0, %1, %2;" : "=r"(r) : "r"(a), "r"(b)); return r; }
__device__ __forceinline__ float2 ln_stats(float sx, float sxx) {
    float mean = sx * (1.0f / DM);
    float var = fmaxf(sxx * (1.0f / DM) - mean * mean, 0.0f);
    float s = bfr(fsqrt(bfr(bfr(var) + 1e-5f)));
    return make_float2(bfr(mean), frcp(s));
}
__device__ __forceinline__ uint32_t ln_apply(uint32_t w, uint32_t m2, float inv) {
    uint32_t d = sub_bf2(w, m2);
    return pk_bf(bf_lo(d) * inv, bf_hi(d) * inv);
}

__device__ __forceinline__ uint32_t ex2_mufu(uint32_t v) { uint32_t r; asm("ex2.approx.f16x2 %0, %1;" : "=r"(r) : "r"(v)); return r; }
__device__ __forceinline__ uint32_t hfma2(uint32_t a, uint32_t b, uint32_t c) { uint32_t r; asm("fma.rn.f16x2 %0, %1, %2, %3;" : "=r"(r) : "r"(a), "r"(b), "r"(c)); return r; }
__device__ __forceinline__ uint32_t ex2_poly(uint32_t w, uint32_t cz, uint32_t ca) {
    uint32_t z;
    asm("lop3.b32 %0, %1, 0x003F003F, %2, 0xEA;" : "=r"(z) : "r"(w), "r"(cz));
    uint32_t q = hfma2(z, ca, 0xE794E794u);
    uint32_t h = hfma2(q, q, 0x7BA97BA9u);
    return __funnelshift_l(w, w, 4) + h;
}
constexpr uint32_t POLY_CZ = 0x3C803C80u, POLY_CA = 0x668D668Du;

struct Params {
    Scratch* g;
    const bf16 *x, *wk, *wv, *wq, *wo, *wr, *wg, *wu, *wd;
    bf16* out;
};

extern __shared__ __align__(1024) uint8_t smem[];

__device__ __noinline__ void attn_safe(const Scratch* G, const bf16* x, const bf16* wq, int row0, int head, uint32_t* res) {
    const int lane = threadIdx.x & 31, half = lane & 1, row = row0 + (lane >> 1);
    const float2 st = ((const float2*)(smem + SM_MISC + MI_STAT))[row & 63];
    float q[18];
#pragma unroll
    for (int d = 0; d < 18; d++) q[d] = 0.f;
#pragma unroll 1
    for (int i = half * 288; i < half * 288 + 288; i++) {
        float xn = bfr(bfr(__bfloat162float(x[row * DM + i]) - st.x) * st.y);
#pragma unroll
        for (int d = 0; d < 18; d++) q[d] += xn * __bfloat162float(wq[i * DM + head * 18 + d]);
    }
#pragma unroll
    for (int d = 0; d < 18; d++) q[d] = bfr(q[d] + __shfl_xor_sync(~0u, q[d], 1)) * 0.23570226039551584f;
    float o[18], l = 0.f, m = -INFINITY;
#pragma unroll
    for (int d = 0; d < 18; d++) o[d] = 0.f;
#pragma unroll 1
    for (int pass = 0; pass < 2; pass++) {
#pragma unroll 1
        for (int k = half * 1024; k < half * 1024 + 1024; k++) {
            const float4* p = G->kvraw + k * 10;
            float4 e = __ldcg(p + 8);
            float s = q[16] * e.x + q[17] * e.y;
#pragma unroll
            for (int j = 0; j < 4; j++) { float4 a = __ldcg(p + j); s += q[4*j] * a.x + q[4*j+1] * a.y + q[4*j+2] * a.z + q[4*j+3] * a.w; }
            if (pass == 0) { m = fmaxf(m, s); }
            else {
                float pr = __expf(s - m);
                l += pr; o[16] += pr * e.z; o[17] += pr * e.w;
#pragma unroll
                for (int j = 0; j < 4; j++) { float4 a = __ldcg(p + 4 + j); o[4*j] += pr * a.x; o[4*j+1] += pr * a.y; o[4*j+2] += pr * a.z; o[4*j+3] += pr * a.w; }
            }
        }
        if (pass == 0) m = fmaxf(m, __shfl_xor_sync(~0u, m, 1));
    }
    l += __shfl_xor_sync(~0u, l, 1);
    const float inv = frcp(l);
    const int g = lane >> 2, t = lane & 3;
#pragma unroll
    for (int p = 0; p < 9; p++) {
        float a = o[2*p] + __shfl_xor_sync(~0u, o[2*p], 1), b = o[2*p+1] + __shfl_xor_sync(~0u, o[2*p+1], 1);
        uint32_t w = pk_bf(a * inv, b * inv);
        uint32_t v0 = __shfl_sync(~0u, w, 2 * g), v1 = __shfl_sync(~0u, w, 2 * g + 16);
        if (p == t) { res[2] = v0; res[3] = v1; }
        if (p == t + 4) { res[4] = v0; res[5] = v1; }
        if (p == 8) { res[0] = v0; res[1] = v1; }
    }
}

#define NSPLIT 4
#define DLY0 400
#define DLYO 0
#define DLY1 200
#define DLY2 400
#define DLY3 500
#define OUT_LATE 1

__device__ __forceinline__ void agent_job(Scratch* G, const CUtensorMap* tm_g, const CUtensorMap* tm_u, int warp, int& st, bool fin) {
    const int cta = blockIdx.x, hg = cta & 3;
    if (warp == 4) {
#pragma unroll 1
        while (st < 4) {
            if (st == 0) {
                constexpr int ZB = sizeof(LLScratch) / NCTA;
#pragma unroll 1
                for (int off = 0; off < ZB; off += 4096) bulk_st_e((uint8_t*)&G->ll + cta * ZB + off, sb + SM_MISC + MI_Z, min(4096, ZB - off));
            } else if (st == 2) {
                if (fin) mbar_wait(BAR(B_OHA)); else if (!mbar_test(BAR(B_OHA))) break;
                bulk_st_e(G->o1[cta], sb + SM_OHI, 9216);
                mbar_wait(BAR(B_ZOK));
                bulk_st_e((uint8_t*)&G->l1 + cta * (sizeof(LLFirst) / NCTA), sb + SM_MISC + MI_Z, sizeof(LLFirst) / NCTA);
            } else {
                asm volatile("cp.async.bulk.wait_group 0;" ::: "memory");
                PROXY_FENCE_GMEM();
                red_relaxed_e(st == 1 ? &G->cnt[32] : G->ll.oflag[cta]);
            }
            asm volatile("cp.async.bulk.commit_group;" ::: "memory");
            st++;
            if (!fin) break;
        }
    } else if (warp == 8) {
        if (st == 0) {
            poll_counter(&G->cnt[32], CNT2);
            mbar_arrive_e(BAR(B_ZOK));
            st = 1;
        } else if (st == 1) {
            const uint32_t* fp = G->ll.oflag[(cta & ~3) + (threadIdx.x & 3)];
            uint32_t f = ld_rlx4(fp);
            if (fin) ll_fix4(f, fp);
            if (__all_sync(~0u, f != 0)) {
                PROXY_FENCE_GMEM();
                mbar_expect_e(BAR(B_OHT), 3 * 9216);
#pragma unroll 1
                for (int u = 1; u < 4; u++) bulk_ld_e(sb + SM_OHI + u * 9216, G->o1[(cta & ~3) + ((hg + u) & 3)], 9216, BAR(B_OHT));
                st = 2;
            }
        }
    } else {
#pragma unroll 1
        while (st < 6) {
            const uint32_t wb = BAR(B_KVD + st);
            if (fin) mbar_wait(wb); else if (!mbar_test(wb)) break;
            if (st == 0 || st == 5) {
                if (st == 0) mbar_expect_e(BAR(B_GU), 4 * 23040);
                mbar_expect_e(BAR(B_WF + (st ? 1 : 0)), st ? 3 * 9216 : 2 * 9216);
                bulk_ld_e(sb + (st ? SM_R : SM_A), G->wo + hg * 10368 + (st ? 2 * 576 : 0), st ? 3 * 9216 : 2 * 9216, BAR(B_WF + (st ? 1 : 0)));
            } else {
                const int fc0 = (cta * 36) & ~7;
                tma2d_e(sb + (st - 1) * 23040, tm_g, fc0, (st - 1) * 144, BAR(B_GU));
                tma2d_e(sb + (st - 1) * 23040 + 11520, tm_u, fc0, (st - 1) * 144, BAR(B_GU));
            }
            st++;
        }
    }
}

__device__ __forceinline__ void load_q(uint32_t* q, int head) {
    const int lane = threadIdx.x & 31, t = lane & 3;
    const uint8_t* qs = smem + SM_A + (((threadIdx.x >> 5) & 3) * 16 + (lane >> 2)) * 304 + head * 36;
    q[0] = *(const uint32_t*)(qs + 4 * t); q[1] = *(const uint32_t*)(qs + 8 * 304 + 4 * t);
    q[2] = *(const uint32_t*)(qs + 16 + 4 * t); q[3] = *(const uint32_t*)(qs + 8 * 304 + 16 + 4 * t);
    q[4] = *(const uint32_t*)(qs + 32); q[5] = *(const uint32_t*)(qs + 8 * 304 + 32);
    if (t != 0) { q[4] = t == 1 ? 0x1800u : 0u; q[5] = q[4]; }
}
__device__ __forceinline__ bool finish_o(const float* o, uint32_t accor, uint32_t* ow) {
    const int src = ((threadIdx.x & 28) | 1);
    const float l0 = __shfl_sync(~0u, o[1], src), l1 = __shfl_sync(~0u, o[3], src);
    const float i0 = frcp(l0), i1 = frcp(l1);
    ow[0] = pk_bf(o[0] * i0, o[1] * i0); ow[1] = pk_bf(o[2] * i1, o[3] * i1);
    ow[2] = pk_bf(o[4] * i0, o[5] * i0); ow[3] = pk_bf(o[6] * i1, o[7] * i1);
    ow[4] = pk_bf(o[8] * i0, o[9] * i0); ow[5] = pk_bf(o[10] * i1, o[11] * i1);
    return __any_sync(~0u, (accor & 0xF800F800u) || !(fminf(l0, l1) >= 64.0f && l0 + l1 <= 1e30f));
}
__device__ __forceinline__ void stage_o(int base, const uint32_t* ow) {
    const int lane = threadIdx.x & 31, t = lane & 3, wg = threadIdx.x >> 7;
    uint8_t* so = smem + base + (((threadIdx.x >> 5) & 3) * 16 + (lane >> 2)) * 16;
    uint8_t* s1 = so + (2 * wg + (t >> 1)) * 1024 + (t & 1) * 8;
    *(uint2*)s1 = make_uint2(ow[2], ow[4]); *(uint2*)(s1 + 128) = make_uint2(ow[3], ow[5]);
    if (t == 3) { *(uint32_t*)(so + 8192 + wg * 4) = ow[0]; *(uint32_t*)(so + 8320 + wg * 4) = ow[1]; }
}

extern "C" __global__ void __launch_bounds__(NTHR, 1)
fused_block(const __grid_constant__ Params P, const __grid_constant__ CUtensorMap tm_x, const __grid_constant__ CUtensorMap tm_wq,
            const __grid_constant__ CUtensorMap tm_wqt, const __grid_constant__ CUtensorMap tm_g,
            const __grid_constant__ CUtensorMap tm_u, const __grid_constant__ CUtensorMap tm_xs,
            const __grid_constant__ CUtensorMap tm_d, const __grid_constant__ CUtensorMap tm_o) {
    const int tid = threadIdx.x, lane = tid & 31;
    const int warp = __shfl_sync(~0u, tid >> 5, 0);
    const int cta = blockIdx.x, qb = cta >> 2, hg = cta & 3;
    const int g = lane >> 2, t = lane & 3;
    uint8_t* const misc = smem + SM_MISC;
    const int wg = warp >> 2, wq4 = warp & 3;
    constexpr uint32_t ONE2 = 0x3F803F80u;
    Scratch* const G = P.g;
    if (warp == 0) { TSG(32); TS(0); }
    uint32_t cp0, cp1, cp2;
    asm volatile("{\n.reg .u64 a, b;\nmov.u64 a, fused_block_param_0;\ncvt.u64.u32 b, %3;\nadd.u64 a, a, b;\n"
                 "ld.param.u32 %0, [a+-120];\nld.param.u32 %1, [a];\nld.param.u32 %2, [a+64];\n}"
                 : "=r"(cp0), "=r"(cp1), "=r"(cp2) : "r"(tid >> 10));
    {
        if (warp < 15) {
            const int cnt = warp < 7 ? 1 : (warp < 12 ? 4 : (warp == 12 ? 2 : 16));
#pragma unroll
            for (int i = 0; i < 4; i++) mbar_init_e(BAR(warp * 4 + i), cnt);
        }
        else l2_prefetch_e(P.x + cta * 16 * DM, 16 * DM * 2);
        if ((uint32_t)__cvta_generic_to_shared(smem) != sb) __trap();
        asm volatile("fence.mbarrier_init.release.cluster;" ::: "memory");
        BAR_SYNC(0, 512);
    }
    if (warp == 0) TS(35);

    if (wg == 0) {
        {
            const CUtensorMap* const mytm = warp == 0 ? &tm_x : (warp == 3 ? &tm_wqt : &tm_wq);
            BAR_SYNC(8, 416);
#pragma unroll 1
            for (int c = 0; c < (warp == 0 ? 9 : 6); c++) {
                mbar_expect_e(BAR(B_FULL + c), warp == 3 ? 2048 : 8192);
                const uint32_t dst = warp == 0 ? SM_X + c * 8192 : ((c + 7) & 7) * 18432 + (warp - 1) * 8192;
                tma2d_e(sb + dst, mytm, warp == 0 ? c * 64 : hg * 144 + (warp - 1) * 64, warp == 0 ? qb * 64 : c * 64, BAR(B_FULL + c));
            }
        }
        if (warp == 0) TS(36);
        BAR_SYNC(1, 416);
        float acc[72];
#pragma unroll 1
        for (int c = 0; c < 9; c++) {
            const uint32_t slot = ((c + 7) & 7) * 1152;
            const uint64_t da = mkdesc(sb + SM_X, 16, 1024, 1) + c * 512;
            const uint64_t db = mkdesc(sb, 8192, 1024, 1) + slot, dt = mkdesc(sb + 16384, 256, 256, 3) + slot;
            mbar_wait(BAR(B_FULL + c));
            if (c == 0) TS(8);
            WG_FENCE();
            wgp_ss_n128_f32_bf16(acc, da, db, c); wgp_ss_n16_f32_bf16(acc + 64, da, dt, c);
#pragma unroll
            for (int s = 1; s < 4; s++) { wg_ss_n128_f32_bf16(acc, da + 2 * s, db + 128 * s); wg_ss_n16_f32_bf16(acc + 64, da + 2 * s, dt + 32 * s); }
            WG_COMMIT();
            WG_WAIT(1);
            mbar_arrive_if(BAR(B_QC + c - 1), lane == 0 && c > 0);
        }
        WG_WAIT(0);
        mbar_arrive_e(BAR(B_QC + 8));
#pragma unroll
        for (int i = 0; i < 72; i++) asm volatile("" : "+f"(acc[i]) :: "memory");
        TS(9);
        mbar_wait(BAR(B_QC + 8));
        mbar_wait(BAR(B_AUX));
        TS(10);
        const float kq = 0.23570226039551584f * 1.4426950408889634f / 512.0f;
        const float2 s0 = ((const float2*)(misc + MI_STAT))[wq4 * 16 + g], s1 = ((const float2*)(misc + MI_STAT))[wq4 * 16 + g + 8];
        const float a0 = s0.y * kq, a1 = s1.y * kq, b0 = -s0.x * a0, b1 = -s1.x * a1;
        const uint32_t qaddr = sb + SM_A + (wq4 * 16 + (lane & 15)) * 304 + (lane >> 4) * 16;
#pragma unroll
        for (int s = 0; s < 9; s++) {
            const float2 c0 = ((const float2*)(misc + MI_CS))[8 * s + t], c1 = ((const float2*)(misc + MI_CS))[8 * s + 4 + t];
            stsm4(qaddr + s * 32,
                  pk_h(fmaf(acc[8*s], a0, c0.x * b0), fmaf(acc[8*s+1], a0, c0.y * b0)), pk_h(fmaf(acc[8*s+2], a1, c0.x * b1), fmaf(acc[8*s+3], a1, c0.y * b1)),
                  pk_h(fmaf(acc[8*s+4], a0, c1.x * b0), fmaf(acc[8*s+5], a0, c1.y * b0)), pk_h(fmaf(acc[8*s+6], a1, c1.x * b1), fmaf(acc[8*s+7], a1, c1.y * b1)));
        }
        TS(43);
    } else if (warp < 13) {
        const int wi = warp - 4, R0 = cta * 16;
        const int r = 2 * wi + (lane >> 4), l = lane & 15;
        float4 a, cs = make_float4(0, 0, 0, 0);
        {
            const int wofs = wi < 8 ? SM_WKV + wi * 4608 : SM_MISC + MP_W;
            mbar_expect_e(BAR(B_W + wi), 4608);
            bulk_ld_e(sb + wofs, P.wk + wi * 1152, 2304, BAR(B_W + wi));
            bulk_ld_e(sb + wofs + 2304, P.wv + wi * 1152, 2304, BAR(B_W + wi));
            BAR_ARRIVE(8, 416);
            const uint4* xp = (const uint4*)(P.x + (R0 + g) * DM + wi * 64) + t;
            uint4 xv[4];
            xv[0] = __ldg(xp); xv[1] = __ldg(xp + 8 * 72); xv[2] = __ldg(xp + 4); xv[3] = __ldg(xp + 8 * 72 + 4);
            mbar_wait(BAR(B_W + wi));
            if (wi == 0) TS(37);
            uint32_t wf[48];
            const uint32_t* wa = (const uint32_t*)(smem + wofs) + 72 * t + g;
            const uint32_t* wc = (const uint32_t*)(smem + wofs) + 72 * t + 8 + (g & 1) * 576;
            float c1[3][4];
#pragma unroll
            for (int i = 0; i < 12; i++) {
                const int s = i / 3, m = i % 3;
                const uint32_t* wp = (m < 2 ? wa + m * 576 : wc) + ((s >> 1) * 32 + (s & 1) * 4) * 9;
                uint32_t w0 = wp[0], w1 = wp[9], w2 = wp[18], w3 = wp[27];
                if (m == 2 && g >= 2) { w0 = ONE2; w1 = ONE2; w2 = ONE2; w3 = ONE2; }
                wf[4*i] = __byte_perm(w0, w1, 0x5410); wf[4*i+1] = __byte_perm(w0, w1, 0x7632);
                wf[4*i+2] = __byte_perm(w2, w3, 0x5410); wf[4*i+3] = __byte_perm(w2, w3, 0x7632);
                if (s == 0) { c1[m][0] = 0.f; c1[m][1] = 0.f; c1[m][2] = 0.f; c1[m][3] = 0.f; }
                mma_bf16(c1[m], wf[4*i], wf[4*i+1], wf[4*i+2], wf[4*i+3], ONE2, ONE2);
            }
            __syncwarp();
            float* pk = (float*)(smem + wofs);
            if (t < 3) *(float2*)(pk + 704 + 16 * t + 2 * g) = t == 0 ? make_float2(c1[0][0], c1[0][2]) : (t == 1 ? make_float2(c1[1][0], c1[1][2]) : make_float2(c1[2][0], c1[2][2]));
            BAR_SYNC(9, 288);
#pragma unroll
            for (int k = 0; k < 9; k++) {
                const float4 v = *(const float4*)(smem + (k < 8 ? SM_WKV + k * 4608 : SM_MISC + MP_W) + 2816 + 16 * min(l, 8));
                cs.x += v.x; cs.y += v.y; cs.z += v.z; cs.w += v.w;
            }
            if (wi == 0) TS(50);
            float ac[6][4], q0 = 0.f, q1 = 0.f;
#pragma unroll
            for (int i = 0; i < 24; i++) ac[i >> 2][i & 3] = 0.f;
#pragma unroll
            for (int s = 0; s < 4; s++) {
#pragma unroll
                for (int n = 0; n < 2; n++) {
                    const uint4 u = xv[(s & 2) + n];
                    const uint32_t b0 = (s & 1) ? u.z : u.x, b1 = (s & 1) ? u.w : u.y;
#pragma unroll
                    for (int m = 0; m < 3; m++) { const int i = 12 * s + 4 * m; mma_bf16(ac[2*m+n], wf[i], wf[i+1], wf[i+2], wf[i+3], b0, b1); }
                    float& q = n ? q1 : q0;
                    q = fmaf(bf_lo(b0), bf_lo(b0), q); q = fmaf(bf_hi(b0), bf_hi(b0), q); q = fmaf(bf_lo(b1), bf_lo(b1), q); q = fmaf(bf_hi(b1), bf_hi(b1), q);
                }
            }
            pk[g * 44 + 40 + t] = q0; pk[(g + 8) * 44 + 40 + t] = q1;
#pragma unroll
            for (int i = 0; i < 6; i++) {
                float* d = pk + (8 * (i & 1) + 2 * t) * 44 + 16 * (i >> 1) + 2 * g;
                if (i < 4 || g < 4) { *(float2*)d = make_float2(ac[i][0], ac[i][2]); *(float2*)(d + 44) = make_float2(ac[i][1], ac[i][3]); }
            }
        }
        if (wi == 0) TS(12);
        BAR_SYNC(1, 416);
        if (wi == 0) TS(38);
        if (wi < 8) {
            a = make_float4(0, 0, 0, 0);
#pragma unroll
            for (int k = 0; k < 9; k++) {
                const float4 u = *(const float4*)(smem + (k < 8 ? SM_WKV + k * 4608 : SM_MISC + MP_W) + r * 176 + 16 * min(l, 10));
                a.x += u.x; a.y += u.y; a.z += u.z; a.w += u.w;
            }
            const float2 st = ln_stats(__shfl_sync(~0u, a.x, (lane & 16) + 9), __shfl_sync(~0u, (a.x + a.y) + (a.z + a.w), (lane & 16) + 10));
            a.x = bfr((a.x - st.x * cs.x) * st.y); a.y = bfr((a.y - st.x * cs.y) * st.y);
            a.z = bfr((a.z - st.x * cs.z) * st.y); a.w = bfr((a.w - st.x * cs.w) * st.y);
            float n2 = a.x * a.x + a.y * a.y;
            const float n8 = __shfl_sync(~0u, n2, (lane & 16) + 8);
            n2 += a.z * a.z + a.w * a.w;
            n2 += __shfl_xor_sync(~0u, n2, 1); n2 += __shfl_xor_sync(~0u, n2, 2);
            if (l == 0) { ((float*)(misc + MP_N2))[r] = n2 + n8; ((float2*)(misc + MP_ST))[r] = st; }
            BAR_SYNC(3, 288);
            if (wi == 0) TS(39);
            const uint32_t mine = ((const uint32_t*)(misc + MP_N2))[r], other = ((const uint32_t*)(misc + MP_N2))[l];
            const uint32_t bal = __ballot_sync(~0u, other > mine || (other == mine && l < r));
            const int rank = __popc((bal >> (lane & 16)) & 0xFFFFu);
            const int blk = (0x76532140u >> (4 * (rank >> 1))) & 7;
            const bool mu = rank < 4;
            const float ks = mu ? 512.f : (1.f / 512.f), vs = mu ? 128.f : -1.f;
            const float s0 = (l & 4) ? vs : ks, s1 = l < 4 ? ks : vs;
            const uint32_t w0 = nz(pk_h(a.x * s0, a.y * s0)), w1 = nz(pk_h(a.z * s1, a.w * s1));
            uint8_t* stg = misc + MP_STG + blk * 160 + (rank & 1) * 16;
            if (l < 8) *(uint2*)(stg + ((l >> 1) + (l >> 2)) * 32 + (l & 1) * 8) = make_uint2(w0, w1);
            if (l == 8) *(uint4*)(stg + 64) = make_uint4(w0, mu ? 0x5800EA00u : 0xBC002840u, 1u, w1);
            if (l == 9 && (rank & 11) == 0) ((uint32_t*)(misc + MP_INFO))[rank >> 2] = mine;
            uint32_t vm = max(__float_as_uint(fabsf(a.z)), __float_as_uint(fabsf(a.w)));
            if (l < 8) vm = max(vm, max(__float_as_uint(fabsf(a.x)), __float_as_uint(fabsf(a.y))));
            vm = __reduce_max_sync(~0u, l >= 4 && l < 9 ? vm : 0u);
            ((uint32_t*)(misc + MP_VM))[wi] = vm;
        } else {
            BAR_SYNC(3, 288);
#pragma unroll 1
            for (int c = 6; c < 9; c++) {
                if (c == 8) mbar_wait(BAR(B_QC + 0));
                const uint32_t slot = sb + (c - 1) * 18432;
                mbar_expect_e(BAR(B_FULL + c), 18432);
                tma2d_e(slot, &tm_wq, hg * 144, c * 64, BAR(B_FULL + c));
                tma2d_e(slot + 8192, &tm_wq, hg * 144 + 64, c * 64, BAR(B_FULL + c));
                tma2d_e(slot + 16384, &tm_wqt, hg * 144 + 128, c * 64, BAR(B_FULL + c));
            }
            uint4 c0[8], c1;
            const uint4* cp = (const uint4*)G->l1.colsum[0][hg];
#pragma unroll
            for (int j = 0; j < 8; j++) c0[j] = ld_rlx16(cp + j * 160 + lane);
            c1 = ld_rlx16(cp + g * 160 + 32 + t);
#pragma unroll 1
            for (int i = 0; i < 8; i++) ((uint4*)(misc + MI_Z))[i * 32 + lane] = make_uint4(0, 0, 0, 0);
            ((uint4*)(misc + MI_ACT))[lane] = make_uint4(0, 0, 0, 0); ((uint4*)(misc + MI_ACT + 384))[lane] = make_uint4(0, 0, 0, 0);
            ((uint32_t*)(misc + MI_KP))[10] = 0;
            PROXY_FENCE_SMEM();
            float4 s = make_float4(0, 0, 0, 0);
#pragma unroll
            for (int j = 0; j < 8; j++) {
                ll_fix16(c0[j], cp + j * 160 + lane, true);
                s.x += __uint_as_float(c0[j].x); s.y += __uint_as_float(c0[j].y); s.z += __uint_as_float(c0[j].z); s.w += __uint_as_float(c0[j].w);
            }
            ((float4*)(misc + MI_CS))[lane] = s;
            const uint4* sp = (const uint4*)(G->l1.stat1 + qb * 64) + lane;
            uint4 sv = ld_rlx16(sp);
            ll_fix16(c1, cp + g * 160 + 32 + t, true);
            const bool u4 = lane & 16, u2 = lane & 8;
            float e0 = __uint_as_float(u4 ? c1.z : c1.x) + __shfl_xor_sync(~0u, __uint_as_float(u4 ? c1.x : c1.z), 16);
            float e1 = __uint_as_float(u4 ? c1.w : c1.y) + __shfl_xor_sync(~0u, __uint_as_float(u4 ? c1.y : c1.w), 16);
            e0 = (u2 ? e1 : e0) + __shfl_xor_sync(~0u, u2 ? e0 : e1, 8);
            e0 += __shfl_xor_sync(~0u, e0, 4);
            ((float*)(misc + MI_CS))[128 + 4 * t + (lane >> 3)] = e0;
            ll_fix16(sv, sp, true);
            ((uint4*)(misc + MI_STAT))[lane] = sv;
            __syncwarp();
            mbar_arrive_e(BAR(B_AUX));
            TS(2);
        }
        if (wi < 8) {
            BAR_SYNC(4, 256);
            if (wi == 0) {
                TS(40);
#pragma unroll
                for (int it = 0; it < 3; it++) {
                    const int i = lane + 32 * it;
                    const uint4 v = ((const uint4*)(misc + MP_STG))[i];
                    if (i < 80) st_rlx16(&G->l1.kv[(qb * 8 + i / 10) * 40 + ((i % 10) >> 1) * 8 + 2 * hg + (i & 1)], v.x, v.y, v.z, v.w);
                }
                const uint4 v = ((const uint4*)(misc + MP_ST))[lane & 7];
                if (lane < 8) st_rlx16((uint4*)(G->l1.stat1 + R0) + lane, nz(v.x), nz(v.y), nz(v.z), nz(v.w));
                TS(51);
                const uint32_t vmx = __reduce_max_sync(~0u, ((const uint32_t*)(misc + MP_VM))[lane & 7]);
                const float2 kn = *(const float2*)(misc + MP_INFO);
                if (lane < 2) G->info[2 * cta + lane] = make_float4(kn.y, kn.x, __uint_as_float(vmx), 0.f);
            }
            if (l < 10) G->kvraw[(R0 + r) * 10 + l] = a;
        }
    } else {
        const int w3 = warp - 13;
        asm volatile("st.shared.v4.u32 [%0], {%1,%2,%3,%3};" :: "r"(sb + SM_MISC + MP_CS + 1024), "r"(cp0), "r"(cp1), "r"(cp2) : "memory");
        if (cta < 72) {
            const int cg = cta % 9, rg = cta / 9;
            uint4 v[6];
#pragma unroll
            for (int j = 0; j < 6; j++) v[j] = __ldg((const uint4*)P.wq + (rg * 72 + w3 * 24 + 4 * j + (lane >> 3)) * 72 + cg * 8 + (lane & 7));
            float s[8];
#pragma unroll
            for (int i = 0; i < 8; i++) s[i] = 0.f;
#pragma unroll
            for (int j = 0; j < 6; j++) {
                s[0] += bf_lo(v[j].x); s[1] += bf_hi(v[j].x); s[2] += bf_lo(v[j].y); s[3] += bf_hi(v[j].y);
                s[4] += bf_lo(v[j].z); s[5] += bf_hi(v[j].z); s[6] += bf_lo(v[j].w); s[7] += bf_hi(v[j].w);
            }
            const bool u4 = lane & 16, u2 = lane & 8;
#pragma unroll
            for (int i = 0; i < 4; i++) s[i] = (u4 ? s[i + 4] : s[i]) + __shfl_xor_sync(~0u, u4 ? s[i] : s[i + 4], 16);
#pragma unroll
            for (int i = 0; i < 2; i++) s[i] = (u2 ? s[i + 2] : s[i]) + __shfl_xor_sync(~0u, u2 ? s[i] : s[i + 2], 8);
            float2* cs = (float2*)(misc + MP_CS);
            cs[w3 * 32 + (lane & 7) * 4 + (lane >> 3)] = make_float2(s[0], s[1]);
            BAR_SYNC(2, 96);
            if (w3 == 0) {
                const float2 a = cs[lane], b = cs[32 + lane], c = cs[64 + lane];
                const int col = cg * 64 + 2 * lane;
                st_rlx8(&G->l1.colsum[rg][col / 144][col % 144], nzf(a.x + b.x + c.x), nzf(a.y + b.y + c.y));
            }
        }
        mbar_wait(BAR(B_FULL + 1));
        if (cta >= 56) {
            const int un = cta - 56, r = un / 36, hs = (un % 36) / 9, w = un % 9;
            uint4 v[6];
#pragma unroll
            for (int e = 0; e < 2; e++) {
                const int d = w < 8 ? 18 * (w >> 1) + 4 * (w & 1) + 2 * e + (t & 1) + 4 * (t & 2) : 18 * (2 * e + (t >> 1)) + 16 + (t & 1);
#pragma unroll
                for (int i = 0; i < 3; i++) v[3*e+i] = __ldg((const uint4*)P.wo + (144 * hs + 72 * r + d) * 72 + (3 * w3 + i) * 8 + g);
            }
#pragma unroll
            for (int i = 0; i < 3; i++) {
                const int cc = (3 * w3 + i) * 8 + g, h2 = cc / 18;
                uint4* dst = G->wo + h2 * 10368 + (36 * r + 9 * ((hs - h2) & 3) + w) * 144 + (cc % 18) * 8 + t;
                dst[0] = v[i]; dst[4] = v[3 + i];
            }
        }
        if (warp == 15) {
            const uint2* wp = (const uint2*)P.wr + lane;
            float s = 0.f;
#pragma unroll
            for (int i = 0; i < 5; i++) if (i < 4 || lane < 16) { const uint2 w = __ldg(wp + 32 * i); s += (bf_lo(w.x) + bf_hi(w.x)) + (bf_lo(w.y) + bf_hi(w.y)); }
#pragma unroll
            for (int d = 1; d < 32; d <<= 1) s += __shfl_xor_sync(~0u, s, d);
            *(float*)(smem + SM_SW) = s;
        }
        if (warp == 13) TS(41);
    }
    const int jrot = cta >> 4;
    if (warp == 4) {
        BAR_SYNC(14, 352);
        red_release_e(&G->cnt[0]);
        TS(13);
        poll_counter(&G->cnt[0], CNT1);
        PROXY_FENCE_GMEM();
        mbar_arrive_e(BAR(B_C1));
        TS(1);
        mbar_wait(BAR(B_QC + 8));
        const int t1 = (jrot + 1) & 7, t2 = (jrot + 2) & 7, n2 = min(8 - t2, 6);
        mbar_expect_e(BAR(B_KV1), 20480);
        bulk_ld_e(sb + 20480, G->l1.kv + t1 * 1280, 20480, BAR(B_KV1));
        mbar_expect_e(BAR(B_KV2), 6 * 20480);
        bulk_ld_e(sb + 2 * 20480, G->l1.kv + t2 * 1280, n2 * 20480, BAR(B_KV2));
        if (n2 < 6) bulk_ld_e(sb + (2 + n2) * 20480, G->l1.kv, (6 - n2) * 20480, BAR(B_KV2));
    } else if (warp > 4 && warp != 12) {
        BAR_ARRIVE(14, 352);
        if (warp > 12) mbar_wait(BAR(B_QC + 2)); else delay(DLY0);
        const int w10 = warp - 5 - (warp > 12);
        const uint4* src = G->l1.kv + jrot * 1280 + w10 * 128 + lane;
        uint4 v[4];
#pragma unroll
        for (int j = 0; j < 4; j++) v[j] = ld_rlx16(src + 32 * j);
        mbar_wait(BAR(B_QC + 2));
#pragma unroll
        for (int j = 0; j < 4; j++) { ll_fix16(v[j], src + 32 * j, true); ((uint4*)smem)[w10 * 128 + lane + 32 * j] = v[j]; }
        PROXY_FENCE_SMEM();
        if (warp == 5) TS(42);
    }
    if (warp != 4) { BAR_SYNC(5, 480); mbar_arrive_if(BAR(B_KV0), tid == 0); }
    else mbar_wait(BAR(B_KV0));
    if (warp == 0) { TS(11); TSG(60); }

    uint32_t ow[6];
    const int orow = wq4 * 16 + g;
    {
        uint32_t q[8], s[64];
        float o[12];
        load_q(q, wg);
        q[6] = *(volatile uint32_t*)(misc + MI_KP + 40); q[7] = *(volatile uint32_t*)(misc + MI_KP + 40);
        const uint32_t cz = POLY_CZ + q[6], ca = POLY_CA + q[6];
        uint32_t accor = 0, chk = 1, redo = 0;
        uint32_t jobs = 0x0102u | (warp == 4 ? 0x5424u : (warp == 8 ? 0xC081u : (warp == 12 ? 0xFA08u : 0u)));
        int st = 0;
        WG_FENCE();
        wgz_rs_n256_f16_f16(s, q[0], q[1], q[2], q[3], mkdesc(sb, 128, 640, 0));
        wg_rs_n256_f16_f16(s, q[4], q[5], q[6], q[7], mkdesc(sb + 256, 128, 640, 0));
        WG_COMMIT();
#pragma unroll 1
        for (int it = 0;; it++) {
            if (__builtin_expect(jobs & 1, 0)) {
                if (it == 0) {
                    if (warp == 8) {
                        mbar_wait(BAR(B_C1));
                        uint32_t kp2 = 0, ka = 0, vm = 0;
#pragma unroll
                        for (int j = 0; j < 4; j++) {
                            const float4 f = __ldcg(G->info + 8 * lane + 2 * j);
                            kp2 = max(kp2, __float_as_uint(f.x)); ka = max(ka, __float_as_uint(f.y)); vm = max(vm, __float_as_uint(f.z));
                        }
                        kp2 = max(kp2, __shfl_xor_sync(~0u, kp2, 1)); kp2 = max(kp2, __shfl_xor_sync(~0u, kp2, 2));
                        ka = __reduce_max_sync(~0u, ka); vm = __reduce_max_sync(~0u, vm);
                        uint32_t* kpp = (uint32_t*)(misc + MI_KP);
                        kpp[(g - jrot) & 7] = kp2;
                        const float kaf = __uint_as_float(ka), vmf = __uint_as_float(vm);
                        kpp[8] = (kaf <= 4096.0f && vmf <= 500.0f && vmf >= 0.015625f) ? ka : 0x7FC00000u;
                        __syncwarp();
                        mbar_arrive_e(BAR(B_INFO));
                    }
                } else if (it == 3) {
                    l2_prefetch_e(P.wg + cta * 20736, 41472); l2_prefetch_e(P.wu + cta * 20736, 41472); l2_prefetch_e(P.wd + cta * 20736, 41472);
                    tm_prefetch_e(&tm_g); tm_prefetch_e(&tm_u); tm_prefetch_e(&tm_d); tm_prefetch_e(&tm_xs); tm_prefetch_e(&tm_o);
                } else if (it != 1 && it != 8) {
                    agent_job(G, &tm_g, &tm_u, warp, st, false);
                } else {
                    mbar_wait(BAR(B_INFO));
                    if (it == 8) {
                        mbar_arrive_e(BAR(B_QRD));
                        if (finish_o(o, accor, ow) || redo) redo = 1;
                        else { stage_o(SM_OHI, ow); PROXY_FENCE_SMEM(); mbar_arrive_e(BAR(B_OHA)); }
                        accor = 0;
                    }
                    float g1[4] = {0, 0, 0, 0}, g2[4] = {0, 0, 0, 0};
                    mma_f16(g1, q[0], q[1], q[2], q[3], q[0], q[2]); mma_f16(g2, q[0], q[1], q[2], q[3], q[1], q[3]);
                    mma_f16(g1, q[4], q[5], q[6], q[7], q[4], q[6]); mma_f16(g2, q[4], q[5], q[6], q[7], q[5], q[7]);
                    const int gm = max(max(__float_as_int(g1[0]), __float_as_int(g1[1])), max(__float_as_int(g2[2]), __float_as_int(g2[3])));
                    const float qn = fmaf(__int_as_float(__reduce_max_sync(~0u, gm)), 262144.0f, -0.99999f);
                    const float kp = ((const float*)(misc + MI_KP))[min(lane, 8)];
                    chk = __ballot_sync(~0u, !(qn * kp <= (lane < 8 ? 222.0f : 4096.0f) && qn <= 4096.0f));
                    if (chk & 0x100) redo |= it == 8 ? 2 : 1;
                    chk >>= it & 1;
                }
            }
            TSL(34 + it);
            if (chk & 1) {
                WG_WAIT(0);
#pragma unroll
                for (int i = 0; i < 64; i++) asm volatile("" : "+r"(s[i]) :: "memory");
#pragma unroll
                for (int i = 0; i < 64; i += 2) if ((i >> 1) & 3) accor |= s[i] | s[i + 1];
            }
            WG_WAIT(0);
#pragma unroll
            for (int i = 0; i < 64; i++) asm volatile("" : "+r"(s[i]) :: "memory");
            const uint64_t dv = mkdesc(sb + 256, 640, 128, 0) + (it & 7) * 1280;
#pragma unroll
            for (int h = 0; h < NSPLIT; h++) {
                constexpr int NR = 64 / NSPLIT;
#pragma unroll
                for (int i = h * NR; i < (h + 1) * NR; i++) s[i] = ((i >> 1) & 3) ? ex2_poly(s[i], cz, ca) : ex2_mufu(s[i]);
#pragma unroll
                for (int i = h * NR; i < (h + 1) * NR; i++) asm volatile("" : "+r"(s[i]) :: "memory");
                WG_FENCE();
#pragma unroll
                for (int c = h * NR / 4; c < (h + 1) * NR / 4; c++) {
                    if (c == 0) wgp_rs_n24_f32_f16(o, s[0], s[1], s[2], s[3], dv, it & 7);
                    else wg_rs_n24_f32_f16(o, s[4*c], s[4*c+1], s[4*c+2], s[4*c+3], dv + c * 80);
                }
            }
            WG_COMMIT();
            if (__builtin_expect((0x83 >> it) & 1, 0)) { if (it == 7) load_q(q, 4 + wg); else mbar_wait(BAR(B_KV1 + it)); }
            chk >>= 1; jobs >>= 1;
            const uint64_t dk = mkdesc(sb, 128, 640, 0) + ((it + 1) & 7) * 1280;
            WG_WAIT(0);
#pragma unroll
            for (int i = 0; i < 12; i++) asm volatile("" : "+f"(o[i]) :: "memory");
            if (it == 15) break;
            WG_FENCE();
            wgz_rs_n256_f16_f16(s, q[0], q[1], q[2], q[3], dk);
            wg_rs_n256_f16_f16(s, q[4], q[5], q[6], q[7], dk + 16);
            WG_COMMIT();
            mbar_arrive_if(BAR(B_KVD - 8 + it), lane == 0 && it - 9u < 5u);
        }
        if (wq4 == 0) TS(18 + wg);
        if (finish_o(o, accor, ow)) redo |= 2;
        if (redo) {
            uint32_t* res = G->tmp[cta][tid];
            if (redo & 1) {
                attn_safe(G, P.x, P.wq, qb * 64 + wq4 * 16, hg * 8 + wg, res);
                stage_o(SM_OHI, res); PROXY_FENCE_SMEM(); mbar_arrive_e(BAR(B_OHA));
            }
            if (redo & 2) {
                attn_safe(G, P.x, P.wq, qb * 64 + wq4 * 16, hg * 8 + 4 + wg, res);
#pragma unroll
                for (int i = 0; i < 6; i++) ow[i] = res[i];
            }
        }
#pragma unroll
        for (int i = 0; i < 6; i++) ow[i] = nz(ow[i]);
        const uint32_t tw = __shfl_sync(~0u, ow[1], lane | 3);
        mbar_wait(BAR(B_ZOK));
        uint8_t* go = (uint8_t*)G->ll.o[cta];
        const uint32_t oa1 = (2 * wg + (t >> 1)) * 1024 + orow * 16 + (t & 1) * 8;
        st_rlx8(go + oa1, ow[2], ow[4]); st_rlx8(go + oa1 + 128, ow[3], ow[5]);
        if (t >= 2) st_rlx4(go + 8192 + wg * 256 + (orow + (t == 2 ? 8 : 0)) * 4, t == 2 ? tw : ow[0]);
        if (wq4 == 0 && st != (0x6240 >> warp & 15)) agent_job(G, &tm_g, &tm_u, warp, st, true);
    }

    uint32_t wf[72];
    if (wg == 0) {
        float acc[72];
        mbar_arrive_e(BAR(B_END));
        mbar_wait(BAR(B_OHT));
        mbar_wait(BAR(B_OHA));
        TS(45); TSG(61);
        const uint4* const wo = G->wo + hg * 10368;
        uint64_t da = mkdesc(sb + SM_OHI, 1024, 128, 0);
#pragma unroll 1
        for (int p = 0; p < 6; p++) {
            if (p == 2) {
                WG_WAIT(0);
                mbar_arrive_e(BAR(B_G4));
                mbar_wait(BAR(B_END));
                TS(44);
                if (warp == 0) {
                    mbar_expect_e(BAR(B_WF + 2), 8 * 4608);
                    bulk_ld_e(sb, wo + 10 * 288, 8 * 4608, BAR(B_WF + 2));
                    mbar_wait(BAR(B_G4));
#pragma unroll 1
                    for (int u = 0; u < 3; u++) {
                        mbar_expect_e(BAR(B_WF + 3 + u), 6 * 4608);
                        bulk_ld_e(sb + (8 + 6 * u) * 4608, wo + (18 + 6 * u) * 288, 6 * 4608, BAR(B_WF + 3 + u));
                    }
                }
                stage_o(SM_OLO, ow);
                PROXY_FENCE_SMEM();
            }
            if (p == 3) {
                TS(3);
                BAR_SYNC(7, 512);
                TS(22);
                da = mkdesc(sb + SM_OLO, 1024, 128, 0);
            }
            uint64_t db = mkdesc(sb, 2304, 128, 0) + (p == 0 ? SM_A / 16 : (p == 1 ? SM_R / 16 : (p == 2 ? 0 : (6 * p - 10) * 288)));
            mbar_wait(BAR(B_WF + p));
            WG_FENCE();
#pragma unroll 1
            for (int u = (0x333432 >> (4 * p)) & 7; u > 0; u--) {
                wgp_ss_n144_f32_bf16(acc, da, db, p | (u ^ 2));
                wg_ss_n144_f32_bf16(acc, da + 128, db + 288);
                da += 256; db += 576;
            }
            WG_COMMIT();
            if (p == 3) { WG_WAIT(1); mbar_arrive_e(BAR(B_G8)); }
        }
        WG_WAIT(0);
        mbar_wait(BAR(B_XS));
#pragma unroll
        for (int i = 0; i < 72; i++) asm volatile("" : "+f"(acc[i]) :: "memory");
        TS(23);
        float sm[4] = {0, 0, 0, 0}, g1[4] = {0, 0, 0, 0}, g2[4] = {0, 0, 0, 0}, g3[4] = {0, 0, 0, 0}, g4[4] = {0, 0, 0, 0};
        const uint32_t xaddr = sb + SM_XS + (wq4 * 16 + (lane & 15)) * 304 + (lane >> 4) * 16;
        const uint8_t* wr = smem + (g == 1 ? SM_XS + 64 * 304 : SM_MISC + MI_ONE) + t * 4;
#pragma unroll
        for (int s = 0; s < 9; s++) {
            uint32_t hw[4];
            ldsm4(hw, xaddr + s * 32);
            const uint32_t w0 = *(const uint32_t*)(wr + s * 32), w1 = *(const uint32_t*)(wr + s * 32 + 16);
#pragma unroll
            for (int i = 0; i < 4; i++) hw[i] = add_bf2(hw[i], pk_bf(acc[8*s+2*i], acc[8*s+2*i+1]));
            mma_bf16(sm, hw[0], hw[1], hw[2], hw[3], w0, w1);
            mma_bf16_k8(g1, hw[0], hw[1], hw[0]); mma_bf16_k8(g2, hw[0], hw[1], hw[1]);
            mma_bf16_k8(g3, hw[2], hw[3], hw[2]); mma_bf16_k8(g4, hw[2], hw[3], hw[3]);
            stsm4(xaddr + s * 32, hw[0], hw[1], hw[2], hw[3]);
        }
        const int dl = (lane & 28) | (g >> 1);
        const float q0 = __shfl_sync(~0u, (g & 1) ? g1[1] + g3[1] : g1[0] + g3[0], dl), q1 = __shfl_sync(~0u, (g & 1) ? g2[3] + g4[3] : g2[2] + g4[2], dl);
        float4* part = G->ll.part[qb][hg] + orow;
        if (t == 0) {
            st_rlx16(part, nzf(sm[0]), nzf(q0), nzf(sm[1]), 1u);
            st_rlx16(part + 8, nzf(sm[2]), nzf(q1), nzf(sm[3]), 1u);
        }
        TS(4);
        __syncwarp();
        delay(DLY1);
        const float4* pin = G->ll.part[qb][t] + orow;
        uint4 p0 = ld_rlx16(pin), p1 = ld_rlx16(pin + 8);
        ll_fix16(p0, pin, true); ll_fix16(p1, pin + 8, true);
        TS(46);
        const bool up = t & 2;
        float v0 = __uint_as_float(up ? p1.x : p0.x) + __shfl_xor_sync(~0u, __uint_as_float(up ? p0.x : p1.x), 2);
        float v1 = __uint_as_float(up ? p1.y : p0.y) + __shfl_xor_sync(~0u, __uint_as_float(up ? p0.y : p1.y), 2);
        float v2 = __uint_as_float(up ? p1.z : p0.z) + __shfl_xor_sync(~0u, __uint_as_float(up ? p0.z : p1.z), 2);
        v0 += __shfl_xor_sync(~0u, v0, 1); v1 += __shfl_xor_sync(~0u, v1, 1); v2 += __shfl_xor_sync(~0u, v2, 1);
        const float2 st = ln_stats(v0, v1);
        uint32_t u = __float_as_uint((v2 - st.x * *(const float*)(smem + SM_SW)) * st.y);
        u ^= ((int)u >> 31) | 0x80000000u;
        const int lr = orow + (t & 2) * 4;
        ((uint32_t*)(misc + MI_CS))[lr] = nz((u & 0xFFFFF800u) | (2047 - (qb * 64 + lr)));
        ((float2*)(misc + MI_STAT))[lr] = st;
        TS(24);
    } else {
        mbar_wait(BAR(B_GU));
        {
            const int mat = lane >> 3;
            const uint32_t wa = sb + wq4 * 23040 + (mat & 1) * 11520 + ((mat >> 1) * 8 + (lane & 7)) * 80 + (wg - 1) * 32;
#pragma unroll
            for (int s = 0; s < 9; s++) { ldsm4t(wf + 8 * s, wa + s * 1280); ldsm4t(wf + 8 * s + 4, wa + s * 1280 + 16); }
        }
        mbar_arrive_e(BAR(B_END));
        mbar_wait(BAR(B_END));
        stage_o(SM_OLO, ow);
        if (DLYO) delay(DLYO);
        const int tl = tid & 127;
        const uint4* src = (const uint4*)G->ll.o[4 * qb + ((hg + wg) & 3)] + tl;
        uint4 v[5];
#pragma unroll
        for (int j = 0; j < 5; j++) if (j < 4 || wq4 < 2) v[j] = ld_rlx16(src + j * 128);
        uint8_t* so = smem + SM_OLO + wg * 9216;
#pragma unroll
        for (int j = 0; j < 4; j++) { ll_fix16(v[j], src + j * 128, true); ((uint4*)so)[tl + j * 128] = v[j]; }
        if (wq4 < 2) {
            ll_fix16(v[4], src + 512, true);
            uint32_t* d = (uint32_t*)(so + 8192 + (tl & 15) * 64 + (tl >> 4) * 4);
            d[0] = v[4].x; d[4] = v[4].y; d[8] = v[4].z; d[12] = v[4].w;
        }
        if (warp == 7) ((uint4*)(misc + MI_ONE))[lane] = make_uint4(ONE2, ONE2, ONE2, ONE2);
        PROXY_FENCE_SMEM();
        BAR_ARRIVE(7, 512);
        if (warp == 4) {
            mbar_wait(BAR(B_G8));
            mbar_expect_e(BAR(B_XS), 64 * 304 + 288);
            tma2d_e(sb + SM_XS, &tm_xs, hg * 144, qb * 64, BAR(B_XS));
            bulk_ld_e(sb + SM_XS + 64 * 304, P.wr + hg * 144, 288, BAR(B_XS));
            mbar_expect_e(BAR(B_DN), 3 * 14400);
            tma2d_e(sb + SM_DN0, &tm_d, 0, cta * 36, BAR(B_DN));
            tma2d_e(sb + SM_DN1, &tm_d, 192, cta * 36, BAR(B_DN));
            tma2d_e(sb + SM_DN2, &tm_d, 384, cta * 36, BAR(B_DN));
        }
    }
    BAR_SYNC(10, 512);

    {
        const uint32_t* keys = (const uint32_t*)(misc + MI_CS);
        const uint32_t ka = keys[lane], kb = keys[lane + 32];
        const uint4 mk = ((const uint4*)keys)[warp];
        const uint32_t my[4] = {mk.x, mk.y, mk.z, mk.w};
        uint32_t rk = 0;
#pragma unroll
        for (int i = 0; i < 4; i++) {
            const uint32_t r = __popc(__ballot_sync(~0u, ka > my[i])) + __popc(__ballot_sync(~0u, kb > my[i]));
            if (r < 8) ((uint32_t*)(misc + MI_TOP))[r] = my[i];
            rk |= r << (8 * i);
        }
        if (warp < 2) {
            BAR_SYNC(12, 512);
            const uint4 v = ((const uint4*)(misc + MI_TOP))[tid & 1];
            st_rlx16(&G->ll.top[hg * 32 + (tid >> 1)][2 * qb + (tid & 1)], v.x, v.y, v.z, v.w);
            if (warp == 0) TS(49);
        } else BAR_ARRIVE(12, 512);
#pragma unroll 1
        for (int i = 0; i < 4; i++, rk >>= 8) {
            if ((rk & 0xF8) == 0 && lane < 18) {
                const int r = 4 * warp + i;
                const uint4 v = *(const uint4*)(smem + SM_XS + r * 304 + lane * 16);
                const float2 st = ((const float2*)(misc + MI_STAT))[r];
                const uint32_t m2 = (__float_as_uint(st.x) >> 16) * 0x10001u;
                uint32_t* pn = G->ll.hn[qb][rk & 7] + hg * 72 + lane * 4;
                st_rlx16(pn, nz(ln_apply(v.x, m2, st.y)), nz(ln_apply(v.y, m2, st.y)), nz(ln_apply(v.z, m2, st.y)), nz(ln_apply(v.w, m2, st.y)));
                st_rlx16(pn + 32 * 8 * 288, nz(v.x), nz(v.y), nz(v.z), nz(v.w));
            }
        }
        __syncwarp();
    }
    uint32_t hsw = 0;
    if (wg == 0) {
#pragma unroll 3
        for (int it = 0; it < 9; it++) {
            const int i = it * 32 + lane, r = wq4 * 16 + i / 18, c = i % 18;
            const uint4 v = *(const uint4*)(smem + SM_XS + r * 304 + c * 16);
            const float2 st = ((const float2*)(misc + MI_STAT))[r];
            const uint32_t m2 = (__float_as_uint(st.x) >> 16) * 0x10001u;
            *(uint4*)(smem + SM_OUT + wq4 * 4608 + i * 16) = make_uint4(add_bf2(v.x, ln_apply(v.x, m2, st.y)), add_bf2(v.y, ln_apply(v.y, m2, st.y)),
                                                                       add_bf2(v.z, ln_apply(v.z, m2, st.y)), add_bf2(v.w, ln_apply(v.w, m2, st.y)));
        }
        PROXY_FENCE_SMEM();
        TS(5);
        BAR_SYNC(11, 512);
        tma2d_st_e(&tm_o, hg * 144, qb * 64 + wq4 * 16, sb + SM_OUT + wq4 * 4608);
        asm volatile("cp.async.bulk.commit_group;\ncp.async.bulk.wait_group 0;" ::: "memory");
        PROXY_FENCE_GMEM();
        TS(6);
        BAR_SYNC(9, 512);
    } else {
        if (wg > 1) {
            const int w8 = warp - 8;
            delay(DLY2);
            const uint4* ks = G->ll.top[cta] + 2 * lane;
            uint4 a = ld_rlx16(ks), b = ld_rlx16(ks + 1);
            ll_fix16(a, ks, true); ll_fix16(b, ks + 1, true);
            if (w8 == 7) TS(25);
            uint32_t pops = 0, key = __reduce_max_sync(~0u, a.x);
#pragma unroll 1
            for (int r = 0; r < w8; r++) {
                if (a.x == key) { a.x = a.y; a.y = a.z; a.z = a.w; a.w = b.x; b.x = b.y; b.y = b.z; b.z = b.w; pops++; }
                key = __reduce_max_sync(~0u, a.x);
            }
            const int tok = 2047 - (key & 2047);
            const uint32_t slot = __shfl_sync(~0u, pops, tok >> 6);
            if (w8 == 7) TS(47);
            const uint4* hp = (const uint4*)G->ll.hn[tok >> 6][slot] + lane;
            uint4 h0 = ld_rlx16(hp), h1 = ld_rlx16(hp + 32), h2 = ld_rlx16(hp + 64 - (lane & 24));
            uint32_t u = (key & 0xFFFFF800u) | 0x400u;
            u ^= (~(int)u >> 31) | 0x80000000u;
            const float sg = bfr(frcp(1.0f + __expf(-bfr(__uint_as_float(u)))));
            ((float4*)(misc + MI_SEL))[w8] = make_float4(__int_as_float(tok), sg, __uint_as_float(slot), 0.f);
            uint4* hd = (uint4*)(smem + SM_HN + w8 * 1168) + lane;
            ll_fix16(h0, hp, true); hd[0] = h0;
            ll_fix16(h1, hp + 32, true); hd[32] = h1;
            ll_fix16(h2, hp + 64, lane < 8);
            if (lane < 8) hd[64] = h2;
        }
        BAR_SYNC(11, OUT_LATE ? 512 : 384);
        if (warp == 4) TS(26);

        const int w12 = warp - 4;
        {
            uint32_t b[20];
#pragma unroll
            for (int i = 0; i < 5; i++) ldsm4(b + 4 * i, sb + SM_HN + (lane & 7) * 1168 + wq4 * 288 + (lane >> 3) * 16 + i * 64);
            float c[4][4];
#pragma unroll
            for (int i = 0; i < 16; i++) c[i >> 2][i & 3] = 0.f;
#pragma unroll
            for (int s = 0; s < 9; s++) {
                mma_bf16(c[s & 1], wf[8*s], wf[8*s+1], wf[8*s+2], wf[8*s+3], b[2*s], b[2*s+1]);
                mma_bf16(c[2 + (s & 1)], wf[8*s+4], wf[8*s+5], wf[8*s+6], wf[8*s+7], b[2*s], b[2*s+1]);
            }
            float4* red = (float4*)(smem + SM_RED) + wq4 * 160 + (wg - 1) * 64 + lane;
            red[0] = make_float4(c[0][0] + c[1][0], c[0][1] + c[1][1], c[0][2] + c[1][2], c[0][3] + c[1][3]);
            if (wg < 3) red[32] = make_float4(c[2][0] + c[3][0], c[2][1] + c[3][1], c[2][2] + c[3][2], c[2][3] + c[3][3]);
        }
        if (warp == 4) TS(27);
        BAR_SYNC(13, 384);
        if (w12 < 5) {
            const float4* red = (const float4*)(smem + SM_RED) + w12 * 32 + lane;
            const float4 a = red[0], b = red[160], c = red[320], d = red[480];
            const float g0 = bfr((a.x + b.x) + (c.x + d.x)), g1 = bfr((a.y + b.y) + (c.y + d.y));
            const float u0 = bfr((a.z + b.z) + (c.z + d.z)), u1 = bfr((a.w + b.w) + (c.w + d.w));
            const float y0 = bfr(g0 * frcp(1.0f + __expf(-g0))) * u0, y1 = bfr(g1 * frcp(1.0f + __expf(-g1))) * u1;
            const int f = 8 * w12 + g - (cta & 1) * 4;
            if (f >= 0 && f < 36) {
                bf16* act = (bf16*)(misc + MI_ACT);
                act[(2 * t) * 56 + f] = __float2bfloat16_rn(y0);
                act[(2 * t + 1) * 56 + f] = __float2bfloat16_rn(y1);
            }
        }
        mbar_wait(BAR(B_DN));
        {
            const int mat = lane >> 3, r = lane & 7;
#pragma unroll
            for (int i = 0; i < 9; i++)
                ldsm4t(wf + 4 * i, sb + (i < 3 ? SM_DN0 : (i < 6 ? SM_DN1 : SM_DN2)) + min(16 * (i % 3) + (mat >> 1) * 8 + r, 35) * 400 + (16 * w12 + (mat & 1) * 8) * 2);
        }
        if (warp == 4) TS(48);
        BAR_SYNC(9, 512);
        if (warp == 4) TS(28);
        {
            uint32_t b[6];
#pragma unroll
            for (int i = 0; i < 6; i++) b[i] = *(const uint32_t*)(misc + MI_ACT + g * 112 + i * 16 + t * 4);
            float c[3][4];
#pragma unroll
            for (int i = 0; i < 12; i++) c[i >> 2][i & 3] = 0.f;
#pragma unroll
            for (int i = 0; i < 9; i++) { const int it = i % 3, s = i / 3, j = 12 * it + 4 * s; mma_bf16(c[it], wf[j], wf[j+1], wf[j+2], wf[j+3], b[2*s], b[2*s+1]); }
#pragma unroll
            for (int it = 0; it < 3; it++) {
                uint32_t* yp = &G->ll.y[2 * (w12 + 12 * it)][cta][lane];
                st_rlx4(yp, nz(pk_bf(c[it][0], c[it][1])));
                st_rlx4(yp + NCTA * 32, nz(pk_bf(c[it][2], c[it][3])));
            }
        }
        if (warp == 4) TS(29);
        if (warp < 6 && cta < 72) {
            const int e = tid & 63;
            const float4 sel = ((const float4*)(misc + MI_SEL))[e & 7];
            const uint32_t* hp = G->ll.hs[__float_as_int(sel.x) >> 6][__float_as_int(sel.z)] + cta * 4 + (e >> 4);
            hsw = ld_rlx4(hp);
            ll_fix4(hsw, hp);
            const uint32_t hnw = ((const uint32_t*)(smem + SM_HN + (e & 7) * 1168))[cta * 4 + (e >> 4)];
            hsw = (e & 8) ? __byte_perm(hsw, hnw, 0x7632) : __byte_perm(hsw, hnw, 0x5410);
        }
    }
    if (cta < 72) {
        if (warp < 4 || warp > 5) delay(warp < 4 ? DLY3 + 250 : DLY3);
        const uint4* src = (const uint4*)G->ll.y[cta] + tid;
        uint4 va = ld_rlx16(src), vb = ld_rlx16(src + 512);
        ll_fix16(va, src, true); ll_fix16(vb, src + 512, true);
        __syncwarp();
        float s[8] = {bf_lo(va.x) + bf_lo(vb.x), bf_hi(va.x) + bf_hi(vb.x), bf_lo(va.y) + bf_lo(vb.y), bf_hi(va.y) + bf_hi(vb.y),
                      bf_lo(va.z) + bf_lo(vb.z), bf_hi(va.z) + bf_hi(vb.z), bf_lo(va.w) + bf_lo(vb.w), bf_hi(va.w) + bf_hi(vb.w)};
        const bool u4 = lane & 16, u2 = lane & 8;
#pragma unroll
        for (int i = 0; i < 4; i++) s[i] = (u4 ? s[i + 4] : s[i]) + __shfl_xor_sync(~0u, u4 ? s[i] : s[i + 4], 16);
#pragma unroll
        for (int i = 0; i < 2; i++) s[i] = (u2 ? s[i + 2] : s[i]) + __shfl_xor_sync(~0u, u2 ? s[i] : s[i + 2], 8);
        *(float2*)(misc + MI_Z + warp * 256 + (lane & 7) * 32 + (lane >> 3) * 8) = make_float2(s[0], s[1]);
        BAR_SYNC(8, 512);
        if (warp == 4) TS(30);
        if (warp == 4 || warp == 5) {
            const int e = tid & 63;
            float y = 0.f;
#pragma unroll
            for (int w = 0; w < 16; w++) y += ((const float*)(misc + MI_Z))[w * 64 + e];
            const float4 sel = ((const float4*)(misc + MI_SEL))[e & 7];
            P.out[__float_as_int(sel.x) * DM + cta * 8 + (e >> 3)] = __float2bfloat16_rn(bf_lo(hsw) + bfr(bf_hi(hsw) + bfr(bfr(y) * sel.y)));
        }
        if (cta == 0 && tid == 0) { G->cnt[0] = 0; G->cnt[32] = 0; }
    }
    if (warp == 4) { TS(31); TSG(33); }
    MARK(99999);
}

typedef CUresult (*EncodeFn)(CUtensorMap*, CUtensorMapDataType, cuuint32_t, void*, const cuuint64_t*, const cuuint64_t*,
                             const cuuint32_t*, const cuuint32_t*, CUtensorMapInterleave, CUtensorMapSwizzle,
                             CUtensorMapL2promotion, CUtensorMapFloatOOBfill);

static void make_map(EncodeFn enc, CUtensorMap* tm, const void* p, int cols, int rows, int bc, int br, CUtensorMapSwizzle sw) {
    cuuint64_t gd[2] = {(cuuint64_t)cols, (cuuint64_t)rows}, gs[1] = {(cuuint64_t)cols * 2};
    cuuint32_t bx[2] = {(cuuint32_t)bc, (cuuint32_t)br}, es[2] = {1, 1};
    enc(tm, CU_TENSOR_MAP_DATA_TYPE_BFLOAT16, 2, (void*)p, gd, gs, bx, es, CU_TENSOR_MAP_INTERLEAVE_NONE, sw,
        CU_TENSOR_MAP_L2_PROMOTION_L2_128B, CU_TENSOR_MAP_FLOAT_OOB_FILL_NONE);
}

extern "C" void kernel_launch(void* const* d_in, const int* in_sizes, int n_in, void* d_out, int out_size) {
    static EncodeFn enc = nullptr;
    static void* scratch = nullptr;
    if (!enc) {
        void* fn = nullptr;
        cudaDriverEntryPointQueryResult qr;
        cudaGetDriverEntryPoint("cuTensorMapEncodeTiled", &fn, cudaEnableDefault, &qr);
        enc = (EncodeFn)fn;
        cudaGetSymbolAddress(&scratch, g_scratch);
        cudaFuncSetAttribute(fused_block, cudaFuncAttributeMaxDynamicSharedMemorySize, SM_TOTAL);
    }
    Params P;
    P.g = (Scratch*)scratch;
    P.x = (const bf16*)d_in[0]; P.wq = (const bf16*)d_in[1]; P.wk = (const bf16*)d_in[2]; P.wv = (const bf16*)d_in[3];
    P.wo = (const bf16*)d_in[4]; P.wr = (const bf16*)d_in[6]; P.wg = (const bf16*)d_in[7]; P.wu = (const bf16*)d_in[8];
    P.wd = (const bf16*)d_in[9]; P.out = (bf16*)d_out;
    CUtensorMap tx, twq, twqt, tg, tu, txs, td, to;
    make_map(enc, &tx, P.x, DM, SEQ, 64, 64, CU_TENSOR_MAP_SWIZZLE_128B);
    make_map(enc, &twq, P.wq, DM, DM, 64, 64, CU_TENSOR_MAP_SWIZZLE_128B);
    make_map(enc, &twqt, P.wq, DM, DM, 16, 64, CU_TENSOR_MAP_SWIZZLE_32B);
    make_map(enc, &tg, P.wg, FF, DM, 40, 144, CU_TENSOR_MAP_SWIZZLE_NONE);
    make_map(enc, &tu, P.wu, FF, DM, 40, 144, CU_TENSOR_MAP_SWIZZLE_NONE);
    make_map(enc, &txs, P.x, DM, SEQ, 152, 64, CU_TENSOR_MAP_SWIZZLE_NONE);
    make_map(enc, &td, P.wd, DM, FF, 200, 36, CU_TENSOR_MAP_SWIZZLE_NONE);
    make_map(enc, &to, P.out, DM, SEQ, 144, 16, CU_TENSOR_MAP_SWIZZLE_NONE);
    fused_block<<<NCTA, NTHR, SM_TOTAL, cudaStreamPerThread>>>(P, tx, twq, twqt, tg, tu, txs, td, to);
}
```

```cpp
#include <cuda_runtime.h>
#include <cuda_bf16.h>
#include <cuda_fp16.h>
#include <cuda.h>
#include <stdint.h>

#define POLY_DEG3 0

__device__ __forceinline__ void wgz_rs_n256_f16_f16(uint32_t* d, uint32_t a0, uint32_t a1, uint32_t a2, uint32_t a3, uint64_t db) {
  asm volatile("{\n.reg .pred p;\nsetp.ne.b32 p, 0, 0;\n"
    "wgmma.mma_async.sync.aligned.m64n256k16.f16.f16.f16 "
    "{%0,%1,%2,%3,%4,%5,%6,%7,%8,%9,%10,%11,%12,%13,%14,%15,%16,%17,%18,%19,%20,%21,%22,%23,%24,%25,%26,%27,%28,%29,%30,%31,%32,%33,%34,%35,%36,%37,%38,%39,%40,%41,%42,%43,%44,%45,%46,%47,%48,%49,%50,%51,%52,%53,%54,%55,%56,%57,%58,%59,%60,%61,%62,%63}, "
    "{%64,%65,%66,%67}, %68, p, 1, 1, 0;\n}\n"
    : "=r"(d[0]), "=r"(d[1]), "=r"(d[2]), "=r"(d[3]), "=r"(d[4]), "=r"(d[5]), "=r"(d[6]), "=r"(d[7]),
      "=r"(d[8]), "=r"(d[9]), "=r"(d[10]), "=r"(d[11]), "=r"(d[12]), "=r"(d[13]), "=r"(d[14]), "=r"(d[15]),
      "=r"(d[16]), "=r"(d[17]), "=r"(d[18]), "=r"(d[19]), "=r"(d[20]), "=r"(d[21]), "=r"(d[22]), "=r"(d[23]),
      "=r"(d[24]), "=r"(d[25]), "=r"(d[26]), "=r"(d[27]), "=r"(d[28]), "=r"(d[29]), "=r"(d[30]), "=r"(d[31]),
      "=r"(d[32]), "=r"(d[33]), "=r"(d[34]), "=r"(d[35]), "=r"(d[36]), "=r"(d[37]), "=r"(d[38]), "=r"(d[39]),
      "=r"(d[40]), "=r"(d[41]), "=r"(d[42]), "=r"(d[43]), "=r"(d[44]), "=r"(d[45]), "=r"(d[46]), "=r"(d[47]),
      "=r"(d[48]), "=r"(d[49]), "=r"(d[50]), "=r"(d[51]), "=r"(d[52]), "=r"(d[53]), "=r"(d[54]), "=r"(d[55]),
      "=r"(d[56]), "=r"(d[57]), "=r"(d[58]), "=r"(d[59]), "=r"(d[60]), "=r"(d[61]), "=r"(d[62]), "=r"(d[63])
    : "r"(a0), "r"(a1), "r"(a2), "r"(a3), "l"(db));
}
__device__ __forceinline__ void wg_rs_n256_f16_f16(uint32_t* d, uint32_t a0, uint32_t a1, uint32_t a2, uint32_t a3, uint64_t db) {
  asm volatile("{\n.reg .pred p;\nsetp.ne.b32 p, 1, 0;\n"
    "wgmma.mma_async.sync.aligned.m64n256k16.f16.f16.f16 "
    "{%0,%1,%2,%3,%4,%5,%6,%7,%8,%9,%10,%11,%12,%13,%14,%15,%16,%17,%18,%19,%20,%21,%22,%23,%24,%25,%26,%27,%28,%29,%30,%31,%32,%33,%34,%35,%36,%37,%38,%39,%40,%41,%42,%43,%44,%45,%46,%47,%48,%49,%50,%51,%52,%53,%54,%55,%56,%57,%58,%59,%60,%61,%62,%63}, "
    "{%64,%65,%66,%67}, %68, p, 1, 1, 0;\n}\n"
    : "+r"(d[0]), "+r"(d[1]), "+r"(d[2]), "+r"(d[3]), "+r"(d[4]), "+r"(d[5]), "+r"(d[6]), "+r"(d[7]),
      "+r"(d[8]), "+r"(d[9]), "+r"(d[10]), "+r"(d[11]), "+r"(d[12]), "+r"(d[13]), "+r"(d[14]), "+r"(d[15]),
      "+r"(d[16]), "+r"(d[17]), "+r"(d[18]), "+r"(d[19]), "+r"(d[20]), "+r"(d[21]), "+r"(d[22]), "+r"(d[23]),
      "+r"(d[24]), "+r"(d[25]), "+r"(d[26]), "+r"(d[27]), "+r"(d[28]), "+r"(d[29]), "+r"(d[30]), "+r"(d[31]),
      "+r"(d[32]), "+r"(d[33]), "+r"(d[34]), "+r"(d[35]), "+r"(d[36]), "+r"(d[37]), "+r"(d[38]), "+r"(d[39]),
      "+r"(d[40]), "+r"(d[41]), "+r"(d[42]), "+r"(d[43]), "+r"(d[44]), "+r"(d[45]), "+r"(d[46]), "+r"(d[47]),
      "+r"(d[48]), "+r"(d[49]), "+r"(d[50]), "+r"(d[51]), "+r"(d[52]), "+r"(d[53]), "+r"(d[54]), "+r"(d[55]),
      "+r"(d[56]), "+r"(d[57]), "+r"(d[58]), "+r"(d[59]), "+r"(d[60]), "+r"(d[61]), "+r"(d[62]), "+r"(d[63])
    : "r"(a0), "r"(a1), "r"(a2), "r"(a3), "l"(db));
}
__device__ __forceinline__ void wg_rs_n24_f32_f16(float* d, uint32_t a0, uint32_t a1, uint32_t a2, uint32_t a3, uint64_t db) {
  asm volatile("{\n.reg .pred p;\nsetp.ne.b32 p, 1, 0;\n"
    "wgmma.mma_async.sync.aligned.m64n24k16.f32.f16.f16 "
    "{%0,%1,%2,%3,%4,%5,%6,%7,%8,%9,%10,%11}, "
    "{%12,%13,%14,%15}, %16, p, 1, 1, 1;\n}\n"
    : "+f"(d[0]), "+f"(d[1]), "+f"(d[2]), "+f"(d[3]), "+f"(d[4]), "+f"(d[5]), "+f"(d[6]), "+f"(d[7]),
      "+f"(d[8]), "+f"(d[9]), "+f"(d[10]), "+f"(d[11])
    : "r"(a0), "r"(a1), "r"(a2), "r"(a3), "l"(db));
}
__device__ __forceinline__ void wgp_rs_n24_f32_f16(float* d, uint32_t a0, uint32_t a1, uint32_t a2, uint32_t a3, uint64_t db, uint32_t sd) {
  asm volatile("{\n.reg .pred p;\nsetp.ne.b32 p, %17, 0;\n"
    "wgmma.mma_async.sync.aligned.m64n24k16.f32.f16.f16 "
    "{%0,%1,%2,%3,%4,%5,%6,%7,%8,%9,%10,%11}, "
    "{%12,%13,%14,%15}, %16, p, 1, 1, 1;\n}\n"
    : "+f"(d[0]), "+f"(d[1]), "+f"(d[2]), "+f"(d[3]), "+f"(d[4]), "+f"(d[5]), "+f"(d[6]), "+f"(d[7]),
      "+f"(d[8]), "+f"(d[9]), "+f"(d[10]), "+f"(d[11])
    : "r"(a0), "r"(a1), "r"(a2), "r"(a3), "l"(db), "r"(sd));
}
__device__ __forceinline__ void wgp_ss_n128_f32_bf16(float* d, uint64_t da, uint64_t db, uint32_t sd) {
  asm volatile("{\n.reg .pred p;\nsetp.ne.b32 p, %66, 0;\n"
    "wgmma.mma_async.sync.aligned.m64n128k16.f32.bf16.bf16 "
    "{%0,%1,%2,%3,%4,%5,%6,%7,%8,%9,%10,%11,%12,%13,%14,%15,%16,%17,%18,%19,%20,%21,%22,%23,%24,%25,%26,%27,%28,%29,%30,%31,%32,%33,%34,%35,%36,%37,%38,%39,%40,%41,%42,%43,%44,%45,%46,%47,%48,%49,%50,%51,%52,%53,%54,%55,%56,%57,%58,%59,%60,%61,%62,%63}, "
    "%64, %65, p, 1, 1, 0, 1;\n}\n"
    : "+f"(d[0]), "+f"(d[1]), "+f"(d[2]), "+f"(d[3]), "+f"(d[4]), "+f"(d[5]), "+f"(d[6]), "+f"(d[7]),
      "+f"(d[8]), "+f"(d[9]), "+f"(d[10]), "+f"(d[11]), "+f"(d[12]), "+f"(d[13]), "+f"(d[14]), "+f"(d[15]),
      "+f"(d[16]), "+f"(d[17]), "+f"(d[18]), "+f"(d[19]), "+f"(d[20]), "+f"(d[21]), "+f"(d[22]), "+f"(d[23]),
      "+f"(d[24]), "+f"(d[25]), "+f"(d[26]), "+f"(d[27]), "+f"(d[28]), "+f"(d[29]), "+f"(d[30]), "+f"(d[31]),
      "+f"(d[32]), "+f"(d[33]), "+f"(d[34]), "+f"(d[35]), "+f"(d[36]), "+f"(d[37]), "+f"(d[38]), "+f"(d[39]),
      "+f"(d[40]), "+f"(d[41]), "+f"(d[42]), "+f"(d[43]), "+f"(d[44]), "+f"(d[45]), "+f"(d[46]), "+f"(d[47]),
      "+f"(d[48]), "+f"(d[49]), "+f"(d[50]), "+f"(d[51]), "+f"(d[52]), "+f"(d[53]), "+f"(d[54]), "+f"(d[55]),
      "+f"(d[56]), "+f"(d[57]), "+f"(d[58]), "+f"(d[59]), "+f"(d[60]), "+f"(d[61]), "+f"(d[62]), "+f"(d[63])
    : "l"(da), "l"(db), "r"(sd));
}
__device__ __forceinline__ void wg_ss_n128_f32_bf16(float* d, uint64_t da, uint64_t db) {
  asm volatile("{\n.reg .pred p;\nsetp.ne.b32 p, 1, 0;\n"
    "wgmma.mma_async.sync.aligned.m64n128k16.f32.bf16.bf16 "
    "{%0,%1,%2,%3,%4,%5,%6,%7,%8,%9,%10,%11,%12,%13,%14,%15,%16,%17,%18,%19,%20,%21,%22,%23,%24,%25,%26,%27,%28,%29,%30,%31,%32,%33,%34,%35,%36,%37,%38,%39,%40,%41,%42,%43,%44,%45,%46,%47,%48,%49,%50,%51,%52,%53,%54,%55,%56,%57,%58,%59,%60,%61,%62,%63}, "
    "%64, %65, p, 1, 1, 0, 1;\n}\n"
    : "+f"(d[0]), "+f"(d[1]), "+f"(d[2]), "+f"(d[3]), "+f"(d[4]), "+f"(d[5]), "+f"(d[6]), "+f"(d[7]),
      "+f"(d[8]), "+f"(d[9]), "+f"(d[10]), "+f"(d[11]), "+f"(d[12]), "+f"(d[13]), "+f"(d[14]), "+f"(d[15]),
      "+f"(d[16]), "+f"(d[17]), "+f"(d[18]), "+f"(d[19]), "+f"(d[20]), "+f"(d[21]), "+f"(d[22]), "+f"(d[23]),
      "+f"(d[24]), "+f"(d[25]), "+f"(d[26]), "+f"(d[27]), "+f"(d[28]), "+f"(d[29]), "+f"(d[30]), "+f"(d[31]),
      "+f"(d[32]), "+f"(d[33]), "+f"(d[34]), "+f"(d[35]), "+f"(d[36]), "+f"(d[37]), "+f"(d[38]), "+f"(d[39]),
      "+f"(d[40]), "+f"(d[41]), "+f"(d[42]), "+f"(d[43]), "+f"(d[44]), "+f"(d[45]), "+f"(d[46]), "+f"(d[47]),
      "+f"(d[48]), "+f"(d[49]), "+f"(d[50]), "+f"(d[51]), "+f"(d[52]), "+f"(d[53]), "+f"(d[54]), "+f"(d[55]),
      "+f"(d[56]), "+f"(d[57]), "+f"(d[58]), "+f"(d[59]), "+f"(d[60]), "+f"(d[61]), "+f"(d[62]), "+f"(d[63])
    : "l"(da), "l"(db));
}
__device__ __forceinline__ void wgp_ss_n16_f32_bf16(float* d, uint64_t da, uint64_t db, uint32_t sd) {
  asm volatile("{\n.reg .pred p;\nsetp.ne.b32 p, %10, 0;\n"
    "wgmma.mma_async.sync.aligned.m64n16k16.f32.bf16.bf16 "
    "{%0,%1,%2,%3,%4,%5,%6,%7}, "
    "%8, %9, p, 1, 1, 0, 1;\n}\n"
    : "+f"(d[0]), "+f"(d[1]), "+f"(d[2]), "+f"(d[3]), "+f"(d[4]), "+f"(d[5]), "+f"(d[6]), "+f"(d[7])
    : "l"(da), "l"(db), "r"(sd));
}
__device__ __forceinline__ void wg_ss_n16_f32_bf16(float* d, uint64_t da, uint64_t db) {
  asm volatile("{\n.reg .pred p;\nsetp.ne.b32 p, 1, 0;\n"
    "wgmma.mma_async.sync.aligned.m64n16k16.f32.bf16.bf16 "
    "{%0,%1,%2,%3,%4,%5,%6,%7}, "
    "%8, %9, p, 1, 1, 0, 1;\n}\n"
    : "+f"(d[0]), "+f"(d[1]), "+f"(d[2]), "+f"(d[3]), "+f"(d[4]), "+f"(d[5]), "+f"(d[6]), "+f"(d[7])
    : "l"(da), "l"(db));
}
__device__ __forceinline__ void wg_rs_n128_f32_bf16(float* d, uint32_t a0, uint32_t a1, uint32_t a2, uint32_t a3, uint64_t db) {
  asm volatile("{\n.reg .pred p;\nsetp.ne.b32 p, 1, 0;\n"
    "wgmma.mma_async.sync.aligned.m64n128k16.f32.bf16.bf16 "
    "{%0,%1,%2,%3,%4,%5,%6,%7,%8,%9,%10,%11,%12,%13,%14,%15,%16,%17,%18,%19,%20,%21,%22,%23,%24,%25,%26,%27,%28,%29,%30,%31,%32,%33,%34,%35,%36,%37,%38,%39,%40,%41,%42,%43,%44,%45,%46,%47,%48,%49,%50,%51,%52,%53,%54,%55,%56,%57,%58,%59,%60,%61,%62,%63}, "
    "{%64,%65,%66,%67}, %68, p, 1, 1, 1;\n}\n"
    : "+f"(d[0]), "+f"(d[1]), "+f"(d[2]), "+f"(d[3]), "+f"(d[4]), "+f"(d[5]), "+f"(d[6]), "+f"(d[7]),
      "+f"(d[8]), "+f"(d[9]), "+f"(d[10]), "+f"(d[11]), "+f"(d[12]), "+f"(d[13]), "+f"(d[14]), "+f"(d[15]),
      "+f"(d[16]), "+f"(d[17]), "+f"(d[18]), "+f"(d[19]), "+f"(d[20]), "+f"(d[21]), "+f"(d[22]), "+f"(d[23]),
      "+f"(d[24]), "+f"(d[25]), "+f"(d[26]), "+f"(d[27]), "+f"(d[28]), "+f"(d[29]), "+f"(d[30]), "+f"(d[31]),
      "+f"(d[32]), "+f"(d[33]), "+f"(d[34]), "+f"(d[35]), "+f"(d[36]), "+f"(d[37]), "+f"(d[38]), "+f"(d[39]),
      "+f"(d[40]), "+f"(d[41]), "+f"(d[42]), "+f"(d[43]), "+f"(d[44]), "+f"(d[45]), "+f"(d[46]), "+f"(d[47]),
      "+f"(d[48]), "+f"(d[49]), "+f"(d[50]), "+f"(d[51]), "+f"(d[52]), "+f"(d[53]), "+f"(d[54]), "+f"(d[55]),
      "+f"(d[56]), "+f"(d[57]), "+f"(d[58]), "+f"(d[59]), "+f"(d[60]), "+f"(d[61]), "+f"(d[62]), "+f"(d[63])
    : "r"(a0), "r"(a1), "r"(a2), "r"(a3), "l"(db));
}
__device__ __forceinline__ void wg_rs_n16_f32_bf16(float* d, uint32_t a0, uint32_t a1, uint32_t a2, uint32_t a3, uint64_t db) {
  asm volatile("{\n.reg .pred p;\nsetp.ne.b32 p, 1, 0;\n"
    "wgmma.mma_async.sync.aligned.m64n16k16.f32.bf16.bf16 "
    "{%0,%1,%2,%3,%4,%5,%6,%7}, "
    "{%8,%9,%10,%11}, %12, p, 1, 1, 1;\n}\n"
    : "+f"(d[0]), "+f"(d[1]), "+f"(d[2]), "+f"(d[3]), "+f"(d[4]), "+f"(d[5]), "+f"(d[6]), "+f"(d[7])
    : "r"(a0), "r"(a1), "r"(a2), "r"(a3), "l"(db));
}
__device__ __forceinline__ void wgp_ss_n144_f32_bf16(float* d, uint64_t da, uint64_t db, uint32_t sd) {
  asm volatile("{\n.reg .pred p;\nsetp.ne.b32 p, %74, 0;\n"
    "wgmma.mma_async.sync.aligned.m64n144k16.f32.bf16.bf16 "
    "{%0,%1,%2,%3,%4,%5,%6,%7,%8,%9,%10,%11,%12,%13,%14,%15,%16,%17,%18,%19,%20,%21,%22,%23,%24,%25,%26,%27,%28,%29,%30,%31,%32,%33,%34,%35,%36,%37,%38,%39,%40,%41,%42,%43,%44,%45,%46,%47,%48,%49,%50,%51,%52,%53,%54,%55,%56,%57,%58,%59,%60,%61,%62,%63,%64,%65,%66,%67,%68,%69,%70,%71}, "
    "%72, %73, p, 1, 1, 0, 1;\n}\n"
    : "+f"(d[0]), "+f"(d[1]), "+f"(d[2]), "+f"(d[3]), "+f"(d[4]), "+f"(d[5]), "+f"(d[6]), "+f"(d[7]),
      "+f"(d[8]), "+f"(d[9]), "+f"(d[10]), "+f"(d[11]), "+f"(d[12]), "+f"(d[13]), "+f"(d[14]), "+f"(d[15]),
      "+f"(d[16]), "+f"(d[17]), "+f"(d[18]), "+f"(d[19]), "+f"(d[20]), "+f"(d[21]), "+f"(d[22]), "+f"(d[23]),
      "+f"(d[24]), "+f"(d[25]), "+f"(d[26]), "+f"(d[27]), "+f"(d[28]), "+f"(d[29]), "+f"(d[30]), "+f"(d[31]),
      "+f"(d[32]), "+f"(d[33]), "+f"(d[34]), "+f"(d[35]), "+f"(d[36]), "+f"(d[37]), "+f"(d[38]), "+f"(d[39]),
      "+f"(d[40]), "+f"(d[41]), "+f"(d[42]), "+f"(d[43]), "+f"(d[44]), "+f"(d[45]), "+f"(d[46]), "+f"(d[47]),
      "+f"(d[48]), "+f"(d[49]), "+f"(d[50]), "+f"(d[51]), "+f"(d[52]), "+f"(d[53]), "+f"(d[54]), "+f"(d[55]),
      "+f"(d[56]), "+f"(d[57]), "+f"(d[58]), "+f"(d[59]), "+f"(d[60]), "+f"(d[61]), "+f"(d[62]), "+f"(d[63]),
      "+f"(d[64]), "+f"(d[65]), "+f"(d[66]), "+f"(d[67]), "+f"(d[68]), "+f"(d[69]), "+f"(d[70]), "+f"(d[71])
    : "l"(da), "l"(db), "r"(sd));
}
__device__ __forceinline__ void wg_ss_n144_f32_bf16(float* d, uint64_t da, uint64_t db) {
  asm volatile("{\n.reg .pred p;\nsetp.ne.b32 p, 1, 0;\n"
    "wgmma.mma_async.sync.aligned.m64n144k16.f32.bf16.bf16 "
    "{%0,%1,%2,%3,%4,%5,%6,%7,%8,%9,%10,%11,%12,%13,%14,%15,%16,%17,%18,%19,%20,%21,%22,%23,%24,%25,%26,%27,%28,%29,%30,%31,%32,%33,%34,%35,%36,%37,%38,%39,%40,%41,%42,%43,%44,%45,%46,%47,%48,%49,%50,%51,%52,%53,%54,%55,%56,%57,%58,%59,%60,%61,%62,%63,%64,%65,%66,%67,%68,%69,%70,%71}, "
    "%72, %73, p, 1, 1, 0, 1;\n}\n"
    : "+f"(d[0]), "+f"(d[1]), "+f"(d[2]), "+f"(d[3]), "+f"(d[4]), "+f"(d[5]), "+f"(d[6]), "+f"(d[7]),
      "+f"(d[8]), "+f"(d[9]), "+f"(d[10]), "+f"(d[11]), "+f"(d[12]), "+f"(d[13]), "+f"(d[14]), "+f"(d[15]),
      "+f"(d[16]), "+f"(d[17]), "+f"(d[18]), "+f"(d[19]), "+f"(d[20]), "+f"(d[21]), "+f"(d[22]), "+f"(d[23]),
      "+f"(d[24]), "+f"(d[25]), "+f"(d[26]), "+f"(d[27]), "+f"(d[28]), "+f"(d[29]), "+f"(d[30]), "+f"(d[31]),
      "+f"(d[32]), "+f"(d[33]), "+f"(d[34]), "+f"(d[35]), "+f"(d[36]), "+f"(d[37]), "+f"(d[38]), "+f"(d[39]),
      "+f"(d[40]), "+f"(d[41]), "+f"(d[42]), "+f"(d[43]), "+f"(d[44]), "+f"(d[45]), "+f"(d[46]), "+f"(d[47]),
      "+f"(d[48]), "+f"(d[49]), "+f"(d[50]), "+f"(d[51]), "+f"(d[52]), "+f"(d[53]), "+f"(d[54]), "+f"(d[55]),
      "+f"(d[56]), "+f"(d[57]), "+f"(d[58]), "+f"(d[59]), "+f"(d[60]), "+f"(d[61]), "+f"(d[62]), "+f"(d[63]),
      "+f"(d[64]), "+f"(d[65]), "+f"(d[66]), "+f"(d[67]), "+f"(d[68]), "+f"(d[69]), "+f"(d[70]), "+f"(d[71])
    : "l"(da), "l"(db));
}

typedef __nv_bfloat16 bf16;
constexpr int SEQ = 2048, DM = 576, FF = 4608;
constexpr int NCTA = 128, NTHR = 512;

struct LLScratch {
    uint32_t o[NCTA][2304];
    uint32_t oflag[NCTA][8];
    uint32_t y[72][NCTA][32];
    uint32_t hn[32][8][288];
    uint32_t hs[32][8][288];
    float4   part[32][4][64];
    uint4    top[NCTA][64];
};
static_assert(sizeof(LLScratch) % (NCTA * 16) == 0, "zero slices");
struct LLFirst {
    uint4 kv[SEQ * 5];
    float2 stat1[SEQ];
    float colsum[36][8][16];
};
static_assert(sizeof(LLFirst) % (NCTA * 16) == 0, "zero slices");
struct Scratch {
    LLScratch ll;
    LLFirst l1;
    uint4 o1[NCTA][576];
    uint4 wo[4 * 36 * 288];
    float4 kvraw[SEQ * 10];
    float4 info[2 * NCTA];
    uint32_t tmp[NCTA][NTHR][8];
    uint32_t cnt[64];
};
__device__ __align__(1024) Scratch g_scratch;
constexpr uint32_t CNT1 = NCTA, CNT2 = NCTA;

#define TS(i)
#define TSG(i)
#define TSL(i)

constexpr int SM_X = 147456;
constexpr int SM_WKV = 92160;
constexpr int SM_OLO = 126976, SM_OHI = 163840;
constexpr int SM_A = 200704;
constexpr int SM_R = 92160;
constexpr int SM_XS = SM_OHI;
constexpr int SM_DN0 = SM_OHI + 20096, SM_DN1 = 0, SM_DN2 = 14464;
constexpr int SM_OUT = SM_OLO + 16384;
constexpr int SM_HN = SM_A, SM_RED = SM_A + 9344;
constexpr int SM_MISC = 221184;
constexpr int SM_BAR = SM_MISC + 10752;
constexpr int SM_TOTAL = 232448;
constexpr int MP_N2 = 1088, MP_ST = 1152, MP_VM = 1280, MP_INFO = 1312, MP_CS = 1344, MP_P = 2304, MP_STG = 2304, MP_B = 3584, MP_W = 5888;
constexpr int MI_STAT = 0;
constexpr int MI_CS = 512;
constexpr int MI_KP = 1088;
constexpr int MI_TOP = 1152;
constexpr int MI_ACT = 1344;
constexpr int MI_SEL = 2304;
constexpr int MI_ONE = 2560;
constexpr int MI_Z = 6400;
constexpr int SM_SW = SM_TOTAL - 16;
constexpr int SM_ZERO = SM_TOTAL - 8;
enum { B_KV1 = 0, B_KV2, B_C1, B_INFO, B_AUX, B_ZOK, B_OHT, B_XS, B_DN, B_GU, B_WF = 19, B_KV0 = 27,
       B_G4 = 28, B_G8, B_QC = 31, B_FULL = 40, B_QRD = 52, B_KVD = 52, B_OHA = 58, B_END, B_W, B_NUM };
static_assert(B_NUM * 8 <= SM_TOTAL - SM_BAR, "barriers");

constexpr uint32_t sb = 1024;
#define BAR(i) (sb + SM_BAR + 8 * (i))

#define MARK(x)
#define MARKMASK 0
#define WG_FENCE() asm volatile("wgmma.fence.sync.aligned;" ::: "memory")
#define WG_COMMIT() asm volatile("wgmma.commit_group.sync.aligned;" ::: "memory")
#define WG_WAIT(n) asm volatile("wgmma.wait_group.sync.aligned %0;" :: "n"(n) : "memory")
#define BAR_SYNC(id, n) asm volatile("barrier.cta.sync %0, %1;" :: "n"(id), "n"(n) : "memory")
#define BAR_ARRIVE(id, n) asm volatile("barrier.cta.arrive %0, %1;" :: "n"(id), "n"(n) : "memory")
#define PROXY_FENCE_GMEM() asm volatile("fence.proxy.async.global;" ::: "memory")
#define PROXY_FENCE_SMEM() asm volatile("fence.proxy.async.shared::cta;" ::: "memory")

__device__ __forceinline__ constexpr uint64_t mkdesc(uint32_t addr, uint32_t lbo, uint32_t sbo, uint32_t mode) {
    return (uint64_t)((addr & 0x3FFFF) >> 4) | ((uint64_t)(lbo >> 4) << 16) | ((uint64_t)(sbo >> 4) << 32) | ((uint64_t)mode << 62);
}
#define ELECT "{\n.reg .pred e;\nelect.sync _|e, 0xffffffff;\n@e "
__device__ __forceinline__ void mbar_init_e(uint32_t b, int c) { asm volatile(ELECT "mbarrier.init.shared::cta.b64 [%0], %1;\n}" :: "r"(b), "r"(c) : "memory"); }
__device__ __forceinline__ void mbar_expect_e(uint32_t b, uint32_t tx) { asm volatile(ELECT "mbarrier.arrive.expect_tx.shared::cta.b64 _, [%0], %1;\n}" :: "r"(b), "r"(tx) : "memory"); }
__device__ __forceinline__ void mbar_arrive_e(uint32_t b) { asm volatile(ELECT "mbarrier.arrive.shared::cta.b64 _, [%0];\n}" :: "r"(b) : "memory"); }
__device__ __forceinline__ void mbar_arrive_if(uint32_t b, bool c) {
    asm volatile("{.reg .pred p; setp.ne.u32 p, %1, 0; @p mbarrier.arrive.shared::cta.b64 _, [%0];}" :: "r"(b), "r"((uint32_t)c) : "memory");
}
__device__ __forceinline__ bool mbar_test(uint32_t b) {
    uint32_t ok;
    asm volatile("{.reg .pred p; mbarrier.test_wait.parity.shared::cta.b64 p, [%1], 0; selp.u32 %0, 1, 0, p;}" : "=r"(ok) : "r"(b) : "memory");
    return __all_sync(~0u, ok);
}
#define GIVEUP "trap;\n"
#define LIMIT "0x20000000"
#define WAITFN template <int LN> __device__ __forceinline__
#define LNDEF(n)
#define SPIN_TAIL "mov.u32 c, %%clock;\nsub.u32 c, c, c0;\nsetp.lt.u32 p, c, " LIMIT ";\n@p bra.uni W;\n" GIVEUP "D:\n}"
WAITFN void mbar_wait_(uint32_t b, uint32_t par) {
    asm volatile("{\n.reg .pred p;\n.reg .u32 c, c0;\n" LNDEF(1)
                 "mbarrier.try_wait.parity.shared::cta.b64 p, [%0], %2;\n@p bra.uni D;\nmov.u32 c0, %%clock;\n"
                 "W: .pragma \"nounroll\";\nmbarrier.try_wait.parity.shared::cta.b64 p, [%0], %2;\n@p bra.uni D;\n" SPIN_TAIL :: "r"(b), "n"(LN), "r"(par) : "memory");
}
#define mbar_wait(b) mbar_wait_<__LINE__>(b, 0)
#define mbar_wait_p(b, p) mbar_wait_<__LINE__>(b, p)
__device__ __forceinline__ void bulk_ld_e(uint32_t dst, const void* src, uint32_t bytes, uint32_t bar) {
    asm volatile(ELECT "cp.async.bulk.shared::cluster.global.mbarrier::complete_tx::bytes [%0], [%1], %2, [%3];\n}"
                 :: "r"(dst), "l"(src), "r"(bytes), "r"(bar) : "memory");
}
__device__ __forceinline__ void bulk_st_e(void* dst, uint32_t src, uint32_t bytes) {
    asm volatile(ELECT "cp.async.bulk.global.shared::cta.bulk_group [%0], [%1], %2;\n}" :: "l"(dst), "r"(src), "r"(bytes) : "memory");
}
__device__ __forceinline__ void tma2d_e(uint32_t dst, const CUtensorMap* tm, int c0, int c1, uint32_t bar) {
    asm volatile(ELECT "cp.async.bulk.tensor.2d.shared::cluster.global.mbarrier::complete_tx::bytes [%0], [%1, {%3, %4}], [%2];\n}"
                 :: "r"(dst), "l"(tm), "r"(bar), "r"(c0), "r"(c1) : "memory");
}
__device__ __forceinline__ void tma2d_st_e(const CUtensorMap* tm, int c0, int c1, uint32_t src) {
    asm volatile(ELECT "cp.async.bulk.tensor.2d.global.shared::cta.bulk_group [%0, {%2, %3}], [%1];\n}" :: "l"(tm), "r"(src), "r"(c0), "r"(c1) : "memory");
}
__device__ __forceinline__ void l2_prefetch_e(const void* src, uint32_t bytes) {
    asm volatile(ELECT "cp.async.bulk.prefetch.L2.global [%0], %1;\n}" :: "l"(src), "r"(bytes) : "memory");
}
__device__ __forceinline__ void tm_prefetch_e(const CUtensorMap* tm) { asm volatile(ELECT "prefetch.tensormap [%0];\n}" :: "l"(tm) : "memory"); }
__device__ __forceinline__ void red_release_e(uint32_t* p) { asm volatile(ELECT "red.release.gpu.global.add.u32 [%0], 1;\n}" :: "l"(p) : "memory"); }
__device__ __forceinline__ void red_relaxed_e(uint32_t* p) { asm volatile(ELECT "red.relaxed.gpu.global.add.u32 [%0], 1;\n}" :: "l"(p) : "memory"); }
WAITFN void poll_counter_(const uint32_t* p, uint32_t target) {
    asm volatile("{\n.reg .pred p;\n.reg .u32 c, c0, v;\n" LNDEF(2) "mov.u32 c0, %%clock;\n"
                 "W: .pragma \"nounroll\";\nld.acquire.gpu.global.u32 v, [%0];\nsetp.ge.u32 p, v, %1;\n@p bra.uni D;\n" SPIN_TAIL
                 :: "l"(p), "r"(target), "n"(LN) : "memory");
}
#define poll_counter(p, t) poll_counter_<__LINE__>(p, t)
__device__ __forceinline__ uint4 ld_rlx16(const void* p) {
    uint4 v;
    asm volatile("ld.relaxed.gpu.global.v4.u32 {%0,%1,%2,%3}, [%4];" : "=r"(v.x), "=r"(v.y), "=r"(v.z), "=r"(v.w) : "l"(p) : "memory");
    return v;
}
__device__ __forceinline__ uint32_t ld_rlx4(const void* p) {
    uint32_t v;
    asm volatile("ld.relaxed.gpu.global.u32 %0, [%1];" : "=r"(v) : "l"(p) : "memory");
    return v;
}
template <int LN, int N, int S> __device__ __forceinline__ void ll_load_(uint4* v, const uint4* p) {
    uint32_t c0;
    asm volatile("mov.u32 %0, %%clock;" : "=r"(c0));
#pragma unroll 1
    while (true) {
        uint32_t m = ~0u;
#pragma unroll
        for (int i = 0; i < N; i++) v[i] = ld_rlx16(p + i * S);
#pragma unroll
        for (int i = 0; i < N; i++) m = min(min(m, v[i].x), min(min(v[i].y, v[i].z), v[i].w));
        if (__all_sync(~0u, m != 0)) break;
        uint32_t stop;
        asm volatile("{\n.reg .pred p;\n.reg .u32 c;\n" LNDEF(2) "mov.u32 %0, 0;\nmov.u32 c, %%clock;\nsub.u32 c, c, %1;\nsetp.lt.u32 p, c, " LIMIT ";\n@p bra.uni D;\n"
                     GIVEUP "mov.u32 %0, 1;\nD:\n}" : "=r"(stop) : "r"(c0), "n"(LN) : "memory");
    }
}
#define ll_load(N, S, v, p) ll_load_<__LINE__, N, S>(v, p)
WAITFN void ll_fix4_(uint32_t& v, const void* p) {
    asm volatile("{\n.reg .pred p, a;\n.reg .u32 c, c0;\n" LNDEF(2) "setp.eq.u32 a, %0, 0;\n"
                 "vote.sync.any.pred p, a, 0xffffffff;\n@!p bra.uni D;\nmov.u32 c0, %%clock;\n"
                 "W: .pragma \"nounroll\";\n@a ld.relaxed.gpu.global.u32 %0, [%1];\nsetp.eq.u32 a, %0, 0;\n"
                 "vote.sync.any.pred p, a, 0xffffffff;\n@!p bra.uni D;\n" SPIN_TAIL
                 : "+r"(v) : "l"(p), "n"(LN) : "memory");
}
#define ll_fix4(v, p) ll_fix4_<__LINE__>(v, p)
__device__ __forceinline__ void st_rlx4(void* p, uint32_t a) { asm volatile("st.relaxed.gpu.global.u32 [%0], %1;" :: "l"(p), "r"(a) : "memory"); }
__device__ __forceinline__ void st_rlx8(void* p, uint32_t a, uint32_t b) { asm volatile("st.relaxed.gpu.global.v2.u32 [%0], {%1,%2};" :: "l"(p), "r"(a), "r"(b) : "memory"); }
__device__ __forceinline__ void st_rlx16(void* p, uint32_t a, uint32_t b, uint32_t c, uint32_t d) {
    asm volatile("st.relaxed.gpu.global.v4.u32 [%0], {%1,%2,%3,%4};" :: "l"(p), "r"(a), "r"(b), "r"(c), "r"(d) : "memory");
}
__device__ __forceinline__ uint32_t nz(uint32_t w) { return max(w, 1u); }
__device__ __forceinline__ uint32_t nzf(float f) { return max(__float_as_uint(f), 1u); }
__device__ __forceinline__ void mma_bf16(float* d, uint32_t a0, uint32_t a1, uint32_t a2, uint32_t a3, uint32_t b0, uint32_t b1) {
    asm volatile("mma.sync.aligned.m16n8k16.row.col.f32.bf16.bf16.f32 {%0,%1,%2,%3}, {%4,%5,%6,%7}, {%8,%9}, {%0,%1,%2,%3};"
                 : "+f"(d[0]), "+f"(d[1]), "+f"(d[2]), "+f"(d[3]) : "r"(a0), "r"(a1), "r"(a2), "r"(a3), "r"(b0), "r"(b1));
}
__device__ __forceinline__ void mma_bf16_k8(float* d, uint32_t a0, uint32_t a1, uint32_t b0) {
    asm volatile("mma.sync.aligned.m16n8k8.row.col.f32.bf16.bf16.f32 {%0,%1,%2,%3}, {%4,%5}, {%6}, {%0,%1,%2,%3};"
                 : "+f"(d[0]), "+f"(d[1]), "+f"(d[2]), "+f"(d[3]) : "r"(a0), "r"(a1), "r"(b0));
}
__device__ __forceinline__ void delay(uint32_t cyc) {
    asm volatile("{\n.reg .pred p;\n.reg .u32 c, c0;\nmov.u32 c0, %%clock;\nW: .pragma \"nounroll\";\nmov.u32 c, %%clock;\nsub.u32 c, c, c0;\n"
                 "setp.lt.u32 p, c, %0;\n@p bra.uni W;\n}" :: "r"(cyc) : "memory");
}
__device__ __forceinline__ int fresh_tid() { int v; asm volatile("mov.u32 %0, %%tid.x;" : "=r"(v)); return v; }
__device__ __forceinline__ float sq_h2(uint32_t w) { float2 f = __half22float2(*(__half2*)&w); return f.x * f.x + f.y * f.y; }
__device__ __forceinline__ void ldsm4(uint32_t* r, uint32_t a) {
    asm volatile("ldmatrix.sync.aligned.m8n8.x4.shared.b16 {%0,%1,%2,%3}, [%4];" : "=r"(r[0]), "=r"(r[1]), "=r"(r[2]), "=r"(r[3]) : "r"(a) : "memory");
}
__device__ __forceinline__ void ldsm4t(uint32_t* r, uint32_t a) {
    asm volatile("ldmatrix.sync.aligned.m8n8.x4.trans.shared.b16 {%0,%1,%2,%3}, [%4];" : "=r"(r[0]), "=r"(r[1]), "=r"(r[2]), "=r"(r[3]) : "r"(a) : "memory");
}
__device__ __forceinline__ void stsm4(uint32_t a, uint32_t r0, uint32_t r1, uint32_t r2, uint32_t r3) {
    asm volatile("stmatrix.sync.aligned.m8n8.x4.shared.b16 [%0], {%1,%2,%3,%4};" :: "r"(a), "r"(r0), "r"(r1), "r"(r2), "r"(r3) : "memory");
}
__device__ __forceinline__ float frcp(float x) { float r; asm("rcp.approx.ftz.f32 %0, %1;" : "=f"(r) : "f"(x)); return r; }
__device__ __forceinline__ float fsqrt(float x) { float r; asm("sqrt.approx.ftz.f32 %0, %1;" : "=f"(r) : "f"(x)); return r; }
__device__ __forceinline__ float bfr(float x) { return __bfloat162float(__float2bfloat16_rn(x)); }
__device__ __forceinline__ uint32_t pk_bf(float lo, float hi) { uint32_t r; asm("cvt.rn.bf16x2.f32 %0, %1, %2;" : "=r"(r) : "f"(hi), "f"(lo)); return r; }
__device__ __forceinline__ uint32_t pk_h(float lo, float hi) { uint32_t r; asm("cvt.rn.f16x2.f32 %0, %1, %2;" : "=r"(r) : "f"(hi), "f"(lo)); return r; }
__device__ __forceinline__ float bf_lo(uint32_t w) { return __uint_as_float(w << 16); }
__device__ __forceinline__ float bf_hi(uint32_t w) { return __uint_as_float(w & 0xFFFF0000u); }
__device__ __forceinline__ uint32_t add_bf2(uint32_t a, uint32_t b) { uint32_t r; asm("add.rn.bf16x2 %0, %1, %2;" : "=r"(r) : "r"(a), "r"(b)); return r; }
__device__ __forceinline__ uint32_t sub_bf2(uint32_t a, uint32_t b) { uint32_t r; asm("sub.rn.bf16x2 %0, %1, %2;" : "=r"(r) : "r"(a), "r"(b)); return r; }
__device__ __forceinline__ float2 ln_stats(float sx, float sxx) {
    float mean = sx * (1.0f / DM);
    float var = fmaxf(sxx * (1.0f / DM) - mean * mean, 0.0f);
    float s = bfr(fsqrt(bfr(bfr(var) + 1e-5f)));
    return make_float2(bfr(mean), frcp(s));
}
__device__ __forceinline__ uint32_t ln_apply(uint32_t w, uint32_t m2, float inv) {
    uint32_t d = sub_bf2(w, m2);
    return pk_bf(bf_lo(d) * inv, bf_hi(d) * inv);
}

__device__ __forceinline__ uint32_t ex2_mufu(uint32_t v) { uint32_t r; asm("ex2.approx.f16x2 %0, %1;" : "=r"(r) : "r"(v)); return r; }
__device__ __forceinline__ uint32_t hfma2(uint32_t a, uint32_t b, uint32_t c) { uint32_t r; asm("fma.rn.f16x2 %0, %1, %2, %3;" : "=r"(r) : "r"(a), "r"(b), "r"(c)); return r; }
__device__ __forceinline__ uint32_t ex2_poly(uint32_t w, uint32_t cz, uint32_t ca) {
    uint32_t z;
    asm("lop3.b32 %0, %1, 0x003F003F, %2, 0xEA;" : "=r"(z) : "r"(w), "r"(cz));
    uint32_t q = hfma2(z, ca, 0xE794E794u);
    uint32_t h = hfma2(q, q, 0x7BA97BA9u);
    return __funnelshift_l(w, w, 4) + h;
}
constexpr uint32_t POLY_CZ = 0x3C803C80u, POLY_CA = 0x668D668Du;

struct Params {
    Scratch* g;
    const bf16 *x, *wk, *wv, *wq, *wo, *wr, *wg, *wu, *wd;
    bf16* out;
};

extern __shared__ __align__(1024) uint8_t smem[];

__device__ __noinline__ void attn_safe(const Scratch* G, const bf16* x, const bf16* wq, int row0, int head, uint32_t* res) {
    const int lane = threadIdx.x & 31, half = lane & 1, row = row0 + (lane >> 1);
    const float2 st = ((const float2*)(smem + SM_MISC + MI_STAT))[row & 63];
    float q[18];
#pragma unroll
    for (int d = 0; d < 18; d++) q[d] = 0.f;
#pragma unroll 1
    for (int i = half * 288; i < half * 288 + 288; i++) {
        float xn = bfr(bfr(__bfloat162float(x[row * DM + i]) - st.x) * st.y);
#pragma unroll
        for (int d = 0; d < 18; d++) q[d] += xn * __bfloat162float(wq[i * DM + head * 18 + d]);
    }
#pragma unroll
    for (int d = 0; d < 18; d++) q[d] = bfr(q[d] + __shfl_xor_sync(~0u, q[d], 1)) * 0.23570226039551584f;
    float o[18], l = 0.f, m = -INFINITY;
#pragma unroll
    for (int d = 0; d < 18; d++) o[d] = 0.f;
#pragma unroll 1
    for (int pass = 0; pass < 2; pass++) {
#pragma unroll 1
        for (int k = half * 1024; k < half * 1024 + 1024; k++) {
            const float4* p = G->kvraw + k * 10;
            float4 e = __ldcg(p + 8);
            float s = q[16] * e.x + q[17] * e.y;
#pragma unroll
            for (int j = 0; j < 4; j++) { float4 a = __ldcg(p + j); s += q[4*j] * a.x + q[4*j+1] * a.y + q[4*j+2] * a.z + q[4*j+3] * a.w; }
            if (pass == 0) { m = fmaxf(m, s); }
            else {
                float pr = __expf(s - m);
                l += pr; o[16] += pr * e.z; o[17] += pr * e.w;
#pragma unroll
                for (int j = 0; j < 4; j++) { float4 a = __ldcg(p + 4 + j); o[4*j] += pr * a.x; o[4*j+1] += pr * a.y; o[4*j+2] += pr * a.z; o[4*j+3] += pr * a.w; }
            }
        }
        if (pass == 0) m = fmaxf(m, __shfl_xor_sync(~0u, m, 1));
    }
    l += __shfl_xor_sync(~0u, l, 1);
    const float inv = frcp(l);
    const int g = lane >> 2, t = lane & 3;
#pragma unroll
    for (int p = 0; p < 9; p++) {
        float a = o[2*p] + __shfl_xor_sync(~0u, o[2*p], 1), b = o[2*p+1] + __shfl_xor_sync(~0u, o[2*p+1], 1);
        uint32_t w = pk_bf(a * inv, b * inv);
        uint32_t v0 = __shfl_sync(~0u, w, 2 * g), v1 = __shfl_sync(~0u, w, 2 * g + 16);
        if (p == t) { res[2] = v0; res[3] = v1; }
        if (p == t + 4) { res[4] = v0; res[5] = v1; }
        if (p == 8) { res[0] = v0; res[1] = v1; }
    }
}

#define NSPLIT 1
#define GATE 1
#define XPF 0
#define QLATE 1
#define DLY0 400
#define DLYO 0
#define DLY1 200
#define DLY2 400
#define DLY3 500
#define OUT_LATE 1

__device__ __forceinline__ void agent_job(Scratch* G, const CUtensorMap* tm_g, const CUtensorMap* tm_u, int warp, int& st, bool fin) {
    const int cta = blockIdx.x, hg = cta & 3;
    if (warp == 4) {
#pragma unroll 1
        while (st < 4) {
            if (st == 0) {
                constexpr int ZB = sizeof(LLScratch) / NCTA;
#pragma unroll 1
                for (int off = 0; off < ZB; off += 4096) bulk_st_e((uint8_t*)&G->ll + cta * ZB + off, sb + SM_MISC + MI_Z, min(4096, ZB - off));
            } else if (st == 2) {
                if (fin) mbar_wait(BAR(B_OHA)); else if (!mbar_test(BAR(B_OHA))) break;
                bulk_st_e(G->o1[cta], sb + SM_OHI, 9216);
                mbar_wait(BAR(B_ZOK));
                bulk_st_e((uint8_t*)&G->l1 + cta * (sizeof(LLFirst) / NCTA), sb + SM_MISC + MI_Z, sizeof(LLFirst) / NCTA);
            } else {
                asm volatile("cp.async.bulk.wait_group 0;" ::: "memory");
                PROXY_FENCE_GMEM();
                red_relaxed_e(st == 1 ? &G->cnt[32] : G->ll.oflag[cta]);
            }
            asm volatile("cp.async.bulk.commit_group;" ::: "memory");
            st++;
            if (!fin) break;
        }
    } else if (warp == 8) {
        if (st == 0) {
            poll_counter(&G->cnt[32], CNT2);
            mbar_arrive_e(BAR(B_ZOK));
            st = 1;
        } else if (st == 1) {
            const uint32_t* fp = G->ll.oflag[(cta & ~3) + (fresh_tid() & 3)];
            uint32_t f = ld_rlx4(fp);
            if (fin) ll_fix4(f, fp);
            if (__all_sync(~0u, f != 0)) {
                PROXY_FENCE_GMEM();
                mbar_expect_e(BAR(B_OHT), 3 * 9216);
#pragma unroll 1
                for (int u = 1; u < 4; u++) bulk_ld_e(sb + SM_OHI + u * 9216, G->o1[(cta & ~3) + ((hg + u) & 3)], 9216, BAR(B_OHT));
                st = 2;
            }
        }
    } else {
#pragma unroll 1
        while (st < 6) {
            const uint32_t wb = BAR(B_KVD + st);
            if (fin) mbar_wait(wb); else if (!mbar_test(wb)) break;
            if (st == 0 || st == 5) {
                if (st == 0) mbar_expect_e(BAR(B_GU), 4 * 23040);
                mbar_expect_e(BAR(B_WF + (st ? 1 : 0)), st ? 3 * 9216 : 2 * 9216);
                bulk_ld_e(sb + (st ? SM_R : SM_A), G->wo + hg * 10368 + (st ? 2 * 576 : 0), st ? 3 * 9216 : 2 * 9216, BAR(B_WF + (st ? 1 : 0)));
            } else {
                const int fc0 = (cta * 36) & ~7;
                tma2d_e(sb + (st - 1) * 23040, tm_g, fc0, (st - 1) * 144, BAR(B_GU));
                tma2d_e(sb + (st - 1) * 23040 + 11520, tm_u, fc0, (st - 1) * 144, BAR(B_GU));
            }
            st++;
        }
    }
}

__device__ __forceinline__ void load_q(uint32_t* q, int head) {
    const int tid = fresh_tid(), t = tid & 3;
    const uint8_t* qs = smem + SM_A + (((tid >> 5) & 3) * 16 + ((tid & 31) >> 2)) * 304 + head * 36;
    q[0] = *(const uint32_t*)(qs + 4 * t); q[1] = *(const uint32_t*)(qs + 8 * 304 + 4 * t);
    q[2] = *(const uint32_t*)(qs + 16 + 4 * t); q[3] = *(const uint32_t*)(qs + 8 * 304 + 16 + 4 * t);
    q[4] = *(const uint32_t*)(qs + 32); q[5] = *(const uint32_t*)(qs + 8 * 304 + 32);
    if (t != 0) { q[4] = t == 1 ? 0x1800u : 0u; q[5] = q[4]; }
}
__device__ __forceinline__ bool finish_o(const float* o, uint32_t accor, uint32_t* ow) {
    const int src = ((fresh_tid() & 28) | 1);
    const float l0 = __shfl_sync(~0u, o[1], src), l1 = __shfl_sync(~0u, o[3], src);
    const float i0 = frcp(l0), i1 = frcp(l1);
    ow[0] = pk_bf(o[0] * i0, o[1] * i0); ow[1] = pk_bf(o[2] * i1, o[3] * i1);
    ow[2] = pk_bf(o[4] * i0, o[5] * i0); ow[3] = pk_bf(o[6] * i1, o[7] * i1);
    ow[4] = pk_bf(o[8] * i0, o[9] * i0); ow[5] = pk_bf(o[10] * i1, o[11] * i1);
    return __any_sync(~0u, (accor & 0xF800F800u) || !(fminf(l0, l1) >= 64.0f && l0 + l1 <= 1e30f));
}
__device__ __forceinline__ void stage_o(int base, const uint32_t* ow) {
    const int tid = fresh_tid(), t = tid & 3, wg = tid >> 7;
    uint8_t* so = smem + base + (((tid >> 5) & 3) * 16 + ((tid & 31) >> 2)) * 16;
    uint8_t* s1 = so + (2 * wg + (t >> 1)) * 1024 + (t & 1) * 8;
    *(uint2*)s1 = make_uint2(ow[2], ow[4]); *(uint2*)(s1 + 128) = make_uint2(ow[3], ow[5]);
    if (t == 3) { *(uint32_t*)(so + 8192 + wg * 4) = ow[0]; *(uint32_t*)(so + 8320 + wg * 4) = ow[1]; }
}

extern "C" __global__ void __launch_bounds__(NTHR, 1)
fused_block(const __grid_constant__ Params P, const __grid_constant__ CUtensorMap tm_x, const __grid_constant__ CUtensorMap tm_wq,
            const __grid_constant__ CUtensorMap tm_wqt, const __grid_constant__ CUtensorMap tm_g,
            const __grid_constant__ CUtensorMap tm_u, const __grid_constant__ CUtensorMap tm_xs,
            const __grid_constant__ CUtensorMap tm_d, const __grid_constant__ CUtensorMap tm_o) {
    int tid = threadIdx.x, lane = tid & 31;
    const int warp = __shfl_sync(~0u, tid >> 5, 0);
    const int cta = blockIdx.x, qb = cta >> 2, hg = cta & 3;
    int g = lane >> 2, t = lane & 3;
    uint8_t* const misc = smem + SM_MISC;
    const int wg = warp >> 2, wq4 = warp & 3;
    constexpr uint32_t ONE2 = 0x3F803F80u;
    Scratch* const G = P.g;
    if (warp == 0) { TSG(32); TS(0); }
    if (warp == 15) {
        uint32_t c0, c1;
        asm volatile("{\n.reg .u64 a, b;\nmov.u64 a, fused_block_param_0;\ncvt.u64.u32 b, %2;\nadd.u64 a, a, b;\n"
                     "ld.param.u32 %0, [a+-120];\nld.param.u32 %1, [a+64];\n}" : "=r"(c0), "=r"(c1) : "r"(tid >> 10));
        mbar_init_e(BAR(B_W), 1);
        mbar_expect_e(BAR(B_W), 2 * 20736);
        bulk_ld_e(sb + SM_WKV, P.wk, 18432, BAR(B_W));
        bulk_ld_e(sb + SM_WKV + 18432, P.wv, 18432, BAR(B_W));
        bulk_ld_e(sb + SM_MISC + MP_W, P.wk + 9216, 2304, BAR(B_W));
        bulk_ld_e(sb + SM_MISC + MP_W + 2304, P.wv + 9216, 2304, BAR(B_W));
        if (XPF) l2_prefetch_e(P.x + cta * 16 * DM, 16 * DM * 2);
        asm volatile("st.shared.v4.u32 [%0], {%1,%2,%3,%3};" :: "r"(sb + SM_SW), "r"(c0), "r"(c1), "r"(0) : "memory");
    } else {
        const int cnt = warp < 7 ? 1 : (warp < 12 ? 4 : (warp == 12 ? 2 : 16));
        asm volatile(ELECT "mbarrier.init.shared::cta.b64 [%0], %1;\n@e mbarrier.init.shared::cta.b64 [%0+8], %1;\n"
                     "@e mbarrier.init.shared::cta.b64 [%0+16], %1;\n@e mbarrier.init.shared::cta.b64 [%0+24], %1;\n"
                     "fence.mbarrier_init.release.cluster;\n}" :: "r"(BAR(warp * 4)), "r"(cnt) : "memory");
    }
    BAR_SYNC(0, 512);
    if (warp == 0) TS(35);

    if (wg == 0) {
        {
            const CUtensorMap* const mytm = warp == 0 ? &tm_x : (warp == 3 ? &tm_wqt : &tm_wq);
            if (QLATE) mbar_wait(BAR(B_W));
#pragma unroll 1
            for (int c = 0; c < (warp == 0 ? 9 : 8); c++) {
                if (c == 6 && warp) BAR_SYNC(8, 384);
                mbar_expect_e(BAR(B_FULL + c), warp == 3 ? 2048 : 8192);
                const uint32_t dst = warp == 0 ? SM_X + c * 8192 : ((c + 7) & 7) * 18432 + (warp - 1) * 8192;
                tma2d_e(sb + dst, mytm, warp == 0 ? c * 64 : hg * 144 + (warp - 1) * 64, warp == 0 ? qb * 64 : c * 64, BAR(B_FULL + c));
            }
        }
        if (warp == 0) TS(36);
        BAR_SYNC(GATE, GATE == 1 ? 416 : 384);
        float acc[72];
#pragma unroll 1
        for (int c = 0; c < 9; c++) {
            const uint32_t slot = ((c + 7) & 7) * 1152;
            const uint64_t da = mkdesc(sb + SM_X, 16, 1024, 1) + c * 512;
            const uint64_t db = mkdesc(sb, 8192, 1024, 1) + slot, dt = mkdesc(sb + 16384, 256, 256, 3) + slot;
            mbar_wait(BAR(B_FULL + c));
            if (c == 0) TS(8);
            WG_FENCE();
            wgp_ss_n128_f32_bf16(acc, da, db, c); wgp_ss_n16_f32_bf16(acc + 64, da, dt, c);
#pragma unroll
            for (int s = 1; s < 4; s++) { wg_ss_n128_f32_bf16(acc, da + 2 * s, db + 128 * s); wg_ss_n16_f32_bf16(acc + 64, da + 2 * s, dt + 32 * s); }
            WG_COMMIT();
            WG_WAIT(1);
            mbar_arrive_if(BAR(B_QC + c - 1), lane == 0 && c > 0);
        }
        mbar_wait(BAR(B_AUX));
        TS(10);
        const float2 s0 = ((const float2*)(misc + MI_STAT))[wq4 * 16 + g], s1 = ((const float2*)(misc + MI_STAT))[wq4 * 16 + g + 8];
        {
            const uint32_t sel = t == 0 ? 0x3232u : (t == 1 ? 0x4432u : 0x4444u), z = *(volatile uint32_t*)(smem + SM_ZERO);
            const uint32_t m0 = __byte_perm(__float_as_uint(-s0.x), 0, sel), m1 = __byte_perm(__float_as_uint(-s1.x), 0, sel);
            WG_FENCE();
            wg_rs_n128_f32_bf16(acc, m0, m1, z, z, mkdesc(sb + SM_MISC + MP_B, 0, 128, 0));
            wg_rs_n16_f32_bf16(acc + 64, m0, m1, z, z, mkdesc(sb + SM_MISC + MP_B + 2048, 0, 128, 0));
            WG_COMMIT();
        }
        WG_WAIT(1);
        mbar_arrive_e(BAR(B_QC + 8));
        const float kq = 0.23570226039551584f * 1.4426950408889634f / 512.0f;
        const float a0 = s0.y * kq, a1 = s1.y * kq;
        const uint32_t qaddr = sb + SM_A + (wq4 * 16 + (lane & 15)) * 304 + (lane >> 4) * 16;
        mbar_wait(BAR(B_QC + 8));
        WG_WAIT(0);
#pragma unroll
        for (int i = 0; i < 72; i++) asm volatile("" : "+f"(acc[i]) :: "memory");
        TS(9);
#pragma unroll
        for (int s = 0; s < 9; s++)
            stsm4(qaddr + s * 32, pk_h(acc[8*s] * a0, acc[8*s+1] * a0), pk_h(acc[8*s+2] * a1, acc[8*s+3] * a1),
                                  pk_h(acc[8*s+4] * a0, acc[8*s+5] * a0), pk_h(acc[8*s+6] * a1, acc[8*s+7] * a1));
        TS(43);
    } else if (warp < 13) {
        const int wi = warp - 4, R0 = cta * 16;
        const int r = 2 * wi + (lane >> 4), l = lane & 15;
        float4 a;
        {
            const int kp = wi / 3, m = wi % 3;
            const uint4* xp = (const uint4*)(P.x + (R0 + g) * DM + kp * 192) + t;
            uint4 xv[12];
#pragma unroll
            for (int i = 0; i < 12; i++) xv[i] = __ldg(xp + (i >> 1) * 4 + (i & 1) * 8 * 72);
            const bool isv = m == 1 || (m == 2 && (g & 1));
            const int wo = 72 * t + (m < 2 ? g : 8);
            const uint32_t* wp = (const uint32_t*)(smem + SM_WKV) + (isv ? 4608 : 0) + kp * 1728 + wo;
            const uint32_t* wl = kp < 2 ? wp + 1152 : (const uint32_t*)(misc + MP_W) + (isv ? 576 : 0) + wo;
            const uint32_t keep = (m == 2 && g >= 2) ? 0u : ~0u;
            uint32_t wf[48];
            float c1[4] = {0, 0, 0, 0};
            mbar_wait(BAR(B_W));
            if (wi == 0) TS(37);
#pragma unroll
            for (int s = 0; s < 12; s++) {
                const uint32_t* p = (s < 8 ? wp + (s >> 1) * 288 : wl + ((s >> 1) - 4) * 288) + (s & 1) * 36;
                const uint32_t w0 = p[0], w1 = p[9], w2 = p[18], w3 = p[27];
                wf[4*s] = (__byte_perm(w0, w1, 0x5410) & keep) | (ONE2 & ~keep); wf[4*s+1] = __byte_perm(w0, w1, 0x7632);
                wf[4*s+2] = (__byte_perm(w2, w3, 0x5410) & keep) | (ONE2 & ~keep); wf[4*s+3] = __byte_perm(w2, w3, 0x7632);
                mma_bf16(c1, wf[4*s], wf[4*s+1], wf[4*s+2], wf[4*s+3], ONE2, ONE2);
            }
            BAR_ARRIVE(8, 384);
            BAR_SYNC(9, 288);
            if (wi == 0) TS(50);
            const float zf = *(volatile float*)(smem + SM_ZERO);
            float* pk = (float*)(misc + MP_P) + kp * 680;
            const bool wr = m < 2 || g < 2;
            if (t == 0 && wr) *(float2*)(pk + 640 + 16 * m + 2 * g) = make_float2(c1[0], c1[2]);
            float ac[4][4], gr[4][4];
#pragma unroll
            for (int i = 0; i < 16; i++) { ac[i >> 2][i & 3] = zf; gr[i >> 2][i & 3] = zf; }
#pragma unroll
            for (int i = 0; i < 12; i++) {
                const int j = 8 * (i >> 1);
                mma_bf16(ac[i & 1], wf[j], wf[j+1], wf[j+2], wf[j+3], xv[i].x, xv[i].y);
                mma_bf16(ac[2 + (i & 1)], wf[j+4], wf[j+5], wf[j+6], wf[j+7], xv[i].z, xv[i].w);
            }
#pragma unroll
            for (int mm = 0; mm < 3; mm++) {
                if (m == mm) {
#pragma unroll
                    for (int i = 4 * mm; i < 4 * mm + 4; i++) {
                        mma_bf16_k8(gr[i & 1], xv[i].x, xv[i].y, xv[i].x); mma_bf16_k8(gr[2 + (i & 1)], xv[i].x, xv[i].y, xv[i].y);
                        mma_bf16_k8(gr[i & 1], xv[i].z, xv[i].w, xv[i].z); mma_bf16_k8(gr[2 + (i & 1)], xv[i].z, xv[i].w, xv[i].w);
                    }
                }
            }
#pragma unroll
            for (int n = 0; n < 2; n++) {
                float* d = pk + (8 * n + 2 * t) * 40 + 16 * m + 2 * g;
                const float e0 = ac[n][0] + ac[2+n][0], e1 = ac[n][1] + ac[2+n][1];
                if (wr) { *(float2*)d = make_float2(e0, ac[n][2] + ac[2+n][2]); *(float2*)(d + 40) = make_float2(e1, ac[n][3] + ac[2+n][3]); }
                else if (g == 2) { d[0] = e0; d[40] = e1; }
                if (t == (g >> 1)) pk[(8 * n + g) * 40 + 37 + m] = (g & 1) ? gr[n][1] + gr[2+n][3] : gr[n][0] + gr[2+n][2];
            }
        }
        if (wi == 0) TS(12);
        BAR_SYNC(1, GATE == 1 ? 416 : 288);
        if (wi == 0) TS(38);
        if (wi < 8) {
            const float4* pa = (const float4*)(misc + MP_P) + r * 10 + min(l, 9), * pc = (const float4*)(misc + MP_P) + 160 + min(l, 8);
            const float4 u0 = pa[0], u1 = pa[170], u2 = pa[340], v0 = pc[0], v1 = pc[170], v2 = pc[340];
            a = make_float4(u0.x + u1.x + u2.x, u0.y + u1.y + u2.y, u0.z + u1.z + u2.z, u0.w + u1.w + u2.w);
            const float4 cs = make_float4(v0.x + v1.x + v2.x, v0.y + v1.y + v2.y, v0.z + v1.z + v2.z, v0.w + v1.w + v2.w);
            const float2 st = ln_stats(__shfl_sync(~0u, a.x, (lane & 16) + 9), __shfl_sync(~0u, a.y + a.z + a.w, (lane & 16) + 9));
            a.x = bfr((a.x - st.x * cs.x) * st.y); a.y = bfr((a.y - st.x * cs.y) * st.y);
            a.z = bfr((a.z - st.x * cs.z) * st.y); a.w = bfr((a.w - st.x * cs.w) * st.y);
            float n2 = a.x * a.x + a.y * a.y;
            const float n8 = __shfl_sync(~0u, n2, (lane & 16) + 8);
            n2 += a.z * a.z + a.w * a.w;
            n2 += __shfl_xor_sync(~0u, n2, 1); n2 += __shfl_xor_sync(~0u, n2, 2);
            if (l == 0) { ((float*)(misc + MP_N2))[r] = n2 + n8; ((float2*)(misc + MP_ST))[r] = st; }
            BAR_ARRIVE(6, 288);
            BAR_SYNC(3, GATE == 3 ? 384 : 256);
            if (wi == 0) TS(39);
            const uint32_t mine = ((const uint32_t*)(misc + MP_N2))[r], other = ((const uint32_t*)(misc + MP_N2))[l];
            const uint32_t bal = __ballot_sync(~0u, other > mine || (other == mine && l < r));
            const int rank = __popc((bal >> (lane & 16)) & 0xFFFFu);
            const int blk = (0x76532140u >> (4 * (rank >> 1))) & 7;
            const bool mu = rank < 4;
            const float ks = mu ? 512.f : (1.f / 512.f), vs = mu ? 128.f : -1.f;
            const float s0 = (l & 4) ? vs : ks, s1 = l < 4 ? ks : vs;
            const uint32_t w0 = nz(pk_h(a.x * s0, a.y * s0)), w1 = nz(pk_h(a.z * s1, a.w * s1));
            uint8_t* stg = misc + MP_STG + blk * 160 + (rank & 1) * 16;
            if (l < 8) *(uint2*)(stg + ((l >> 1) + (l >> 2)) * 32 + (l & 1) * 8) = make_uint2(w0, w1);
            if (l == 8) *(uint4*)(stg + 64) = make_uint4(w0, mu ? 0x5800EA00u : 0xBC002840u, 1u, w1);
            if (l == 9 && (rank & 11) == 0) ((uint32_t*)(misc + MP_INFO))[rank >> 2] = mine;
            uint32_t vm = max(__float_as_uint(fabsf(a.z)), __float_as_uint(fabsf(a.w)));
            if (l < 8) vm = max(vm, max(__float_as_uint(fabsf(a.x)), __float_as_uint(fabsf(a.y))));
            vm = __reduce_max_sync(~0u, l >= 4 && l < 9 ? vm : 0u);
            ((uint32_t*)(misc + MP_VM))[wi] = vm;
        } else {
            uint4 c0[9];
            ll_load(9, 32, c0, (const uint4*)G->l1.colsum[9 * hg] + lane);
            TS(52);
            BAR_SYNC(6, 288);
#pragma unroll 1
            for (int i = 0; i < 13; i++) ((uint4*)(misc + MI_Z + 4096 - 13 * 512))[i * 32 + lane] = make_uint4(0, 0, 0, 0);
            ((uint4*)(misc + MP_B))[lane] = make_uint4(0, 0, 0, 0);
            __syncwarp();
            const bool u4 = lane & 16, u2 = lane & 8;
            bf16* bp = (bf16*)(misc + MP_B) + (t >> 1) * 64 + (t & 1) * 4 + (lane >> 3) + (g & 1) * 8;
#pragma unroll
            for (int i = 0; i < 9; i++) {
                float e0 = __uint_as_float(u4 ? c0[i].z : c0[i].x) + __shfl_xor_sync(~0u, __uint_as_float(u4 ? c0[i].x : c0[i].z), 16);
                float e1 = __uint_as_float(u4 ? c0[i].w : c0[i].y) + __shfl_xor_sync(~0u, __uint_as_float(u4 ? c0[i].y : c0[i].w), 16);
                e0 = (u2 ? e1 : e0) + __shfl_xor_sync(~0u, u2 ? e0 : e1, 8);
                e0 += __shfl_xor_sync(~0u, e0, 4);
                const float hi = bfr(e0), mid = bfr(e0 - hi);
                bp[128 * i] = __float2bfloat16_rn((g & 1) ? mid : hi);
                if (g & 1) bp[128 * i + 8] = __float2bfloat16_rn(e0 - hi - mid);
            }
            PROXY_FENCE_SMEM();
            ll_load(1, 0, c0, (const uint4*)(G->l1.stat1 + qb * 64) + lane);
            ((uint4*)(misc + MI_STAT))[lane] = c0[0];
            __syncwarp();
            mbar_arrive_e(BAR(B_AUX));
            TS(2);
        }
        if (wi < 8) {
            BAR_SYNC(4, GATE == 4 ? 384 : 256);
            if (wi == 0) {
                TS(40);
#pragma unroll
                for (int it = 0; it < 3; it++) {
                    const int i = lane + 32 * it;
                    const uint4 v = ((const uint4*)(misc + MP_STG))[i];
                    if (i < 80) st_rlx16(&G->l1.kv[(qb * 8 + i / 10) * 40 + ((i % 10) >> 1) * 8 + 2 * hg + (i & 1)], v.x, v.y, v.z, v.w);
                }
                const uint4 v = ((const uint4*)(misc + MP_ST))[lane & 7];
                if (lane < 8) st_rlx16((uint4*)(G->l1.stat1 + R0) + lane, nz(v.x), nz(v.y), nz(v.z), nz(v.w));
                TS(51);
                const uint32_t vmx = __reduce_max_sync(~0u, ((const uint32_t*)(misc + MP_VM))[lane & 7]);
                const float2 kn = *(const float2*)(misc + MP_INFO);
                if (lane < 2) G->info[2 * cta + lane] = make_float4(kn.y, kn.x, __uint_as_float(vmx), 0.f);
            }
            if (l < 10) G->kvraw[(R0 + r) * 10 + l] = a;
        }
    } else {
        const int w3 = warp - 13;
        if (cta < 72) {
            const int cg = cta % 9, rg = cta / 9;
            uint4 v[6];
#pragma unroll
            for (int j = 0; j < 6; j++) v[j] = __ldg((const uint4*)P.wq + (rg * 72 + w3 * 24 + 4 * j + (lane >> 3)) * 72 + cg * 8 + (lane & 7));
            float s[8];
#pragma unroll
            for (int i = 0; i < 8; i++) s[i] = 0.f;
#pragma unroll
            for (int j = 0; j < 6; j++) {
                s[0] += bf_lo(v[j].x); s[1] += bf_hi(v[j].x); s[2] += bf_lo(v[j].y); s[3] += bf_hi(v[j].y);
                s[4] += bf_lo(v[j].z); s[5] += bf_hi(v[j].z); s[6] += bf_lo(v[j].w); s[7] += bf_hi(v[j].w);
            }
            const bool u4 = lane & 16, u2 = lane & 8;
#pragma unroll
            for (int i = 0; i < 4; i++) s[i] = (u4 ? s[i + 4] : s[i]) + __shfl_xor_sync(~0u, u4 ? s[i] : s[i + 4], 16);
#pragma unroll
            for (int i = 0; i < 2; i++) s[i] = (u2 ? s[i + 2] : s[i]) + __shfl_xor_sync(~0u, u2 ? s[i] : s[i + 2], 8);
            float2* cs = (float2*)(misc + MP_CS);
            cs[w3 * 32 + (lane & 7) * 4 + (lane >> 3)] = make_float2(s[0], s[1]);
            BAR_SYNC(2, 96);
            if (w3 == 0) {
                const float2 a = cs[lane], b = cs[32 + lane], c = cs[64 + lane];
                st_rlx8(&G->l1.colsum[4 * cg + (lane >> 3)][rg][2 * (lane & 7)], nzf(a.x + b.x + c.x), nzf(a.y + b.y + c.y));
            }
        }
        mbar_wait(BAR(B_FULL + 1));
        if (cta >= 56) {
            const int un = cta - 56, r = un / 36, hs = (un % 36) / 9, w = un % 9;
            uint4 v[6];
#pragma unroll
            for (int e = 0; e < 2; e++) {
                const int d = w < 8 ? 18 * (w >> 1) + 4 * (w & 1) + 2 * e + (t & 1) + 4 * (t & 2) : 18 * (2 * e + (t >> 1)) + 16 + (t & 1);
#pragma unroll
                for (int i = 0; i < 3; i++) v[3*e+i] = __ldg((const uint4*)P.wo + (144 * hs + 72 * r + d) * 72 + (3 * w3 + i) * 8 + g);
            }
#pragma unroll
            for (int i = 0; i < 3; i++) {
                const int cc = (3 * w3 + i) * 8 + g, h2 = cc / 18;
                uint4* dst = G->wo + h2 * 10368 + (36 * r + 9 * ((hs - h2) & 3) + w) * 144 + (cc % 18) * 8 + t;
                dst[0] = v[i]; dst[4] = v[3 + i];
            }
        }
        if (warp == 14) {
            mbar_wait(BAR(B_QC + 0));
            mbar_expect_e(BAR(B_FULL + 8), 18432);
            tma2d_e(sb + 7 * 18432, &tm_wq, hg * 144, 512, BAR(B_FULL + 8));
            tma2d_e(sb + 7 * 18432 + 8192, &tm_wq, hg * 144 + 64, 512, BAR(B_FULL + 8));
            tma2d_e(sb + 7 * 18432 + 16384, &tm_wqt, hg * 144 + 128, 512, BAR(B_FULL + 8));
        }
        if (warp == 15) {
            if ((uint32_t)__cvta_generic_to_shared(smem) != sb) __trap();
            const uint2* wp = (const uint2*)P.wr + lane;
            float s = 0.f;
#pragma unroll
            for (int i = 0; i < 5; i++) if (i < 4 || lane < 16) { const uint2 w = __ldg(wp + 32 * i); s += (bf_lo(w.x) + bf_hi(w.x)) + (bf_lo(w.y) + bf_hi(w.y)); }
#pragma unroll
            for (int d = 1; d < 32; d <<= 1) s += __shfl_xor_sync(~0u, s, d);
            *(float*)(smem + SM_SW) = s;
        }
        if (warp == 13) TS(41);
    }
    const int jrot = cta >> 4;
    if (warp == 4) {
        BAR_SYNC(14, 352);
        red_release_e(&G->cnt[0]);
        TS(13);
        poll_counter(&G->cnt[0], CNT1);
        PROXY_FENCE_GMEM();
        mbar_arrive_e(BAR(B_C1));
        TS(1);
        mbar_wait(BAR(B_QC + 8));
        const int t1 = (jrot + 1) & 7, t2 = (jrot + 2) & 7, n2 = min(8 - t2, 6);
        mbar_expect_e(BAR(B_KV1), 20480);
        bulk_ld_e(sb + 20480, G->l1.kv + t1 * 1280, 20480, BAR(B_KV1));
        mbar_expect_e(BAR(B_KV2), 6 * 20480);
        bulk_ld_e(sb + 2 * 20480, G->l1.kv + t2 * 1280, n2 * 20480, BAR(B_KV2));
        if (n2 < 6) bulk_ld_e(sb + (2 + n2) * 20480, G->l1.kv, (6 - n2) * 20480, BAR(B_KV2));
    } else if (warp > 4 && warp != 12) {
        BAR_ARRIVE(14, 352);
        if (warp > 12) mbar_wait(BAR(B_QC + 0)); else delay(DLY0);
        const int w10 = warp - 5 - (warp > 12);
        const uint4* src = G->l1.kv + jrot * 1280 + w10 * 128 + lane;
        uint4 v[4];
        ll_load(4, 32, v, src);
        mbar_wait(BAR(B_QC + 2));
#pragma unroll
        for (int j = 0; j < 4; j++) ((uint4*)smem)[w10 * 128 + lane + 32 * j] = v[j];
        PROXY_FENCE_SMEM();
        if (warp == 5) TS(42);
    }
    if (warp != 4) { BAR_SYNC(5, 480); mbar_arrive_if(BAR(B_KV0), tid == 0); }
    else mbar_wait(BAR(B_KV0));
    if (warp == 0) { TS(11); TSG(60); }

    uint32_t ow[6];
    {
        uint32_t q[8], s[64];
        float o[12];
        load_q(q, wg);
        q[6] = *(volatile uint32_t*)(smem + SM_ZERO); q[7] = *(volatile uint32_t*)(smem + SM_ZERO);
        const uint32_t cz = POLY_CZ + q[6], ca = POLY_CA + q[6];
        uint32_t accor = 0, chk = 1, redo = 0;
        uint32_t jobs = 0x0102u | (warp == 4 ? 0x5424u : (warp == 8 ? 0xC081u : (warp == 12 ? 0xFA08u : 0u)));
        int st = 0;
        WG_FENCE();
        wgz_rs_n256_f16_f16(s, q[0], q[1], q[2], q[3], mkdesc(sb, 128, 640, 0));
        wg_rs_n256_f16_f16(s, q[4], q[5], q[6], q[7], mkdesc(sb + 256, 128, 640, 0));
        WG_COMMIT();
#pragma unroll 1
        for (int it = 0;; it++) {
            if (__builtin_expect(jobs & 1, 0)) {
                const int lane = fresh_tid() & 31, g = lane >> 2, t = lane & 3;
                if (it == 0) {
                    if (warp == 8) {
                        mbar_wait(BAR(B_C1));
                        uint32_t kp2 = 0, ka = 0, vm = 0;
#pragma unroll
                        for (int j = 0; j < 4; j++) {
                            const float4 f = __ldcg(G->info + 8 * lane + 2 * j);
                            kp2 = max(kp2, __float_as_uint(f.x)); ka = max(ka, __float_as_uint(f.y)); vm = max(vm, __float_as_uint(f.z));
                        }
                        kp2 = max(kp2, __shfl_xor_sync(~0u, kp2, 1)); kp2 = max(kp2, __shfl_xor_sync(~0u, kp2, 2));
                        ka = __reduce_max_sync(~0u, ka); vm = __reduce_max_sync(~0u, vm);
                        uint32_t* kpp = (uint32_t*)(misc + MI_KP);
                        kpp[(g - jrot) & 7] = kp2;
                        const float kaf = __uint_as_float(ka), vmf = __uint_as_float(vm);
                        kpp[8] = (kaf <= 4096.0f && vmf <= 500.0f && vmf >= 0.015625f) ? ka : 0x7FC00000u;
                        __syncwarp();
                        mbar_arrive_e(BAR(B_INFO));
                    }
                } else if (it == 3) {
                    l2_prefetch_e(P.wg + cta * 20736, 41472); l2_prefetch_e(P.wu + cta * 20736, 41472); l2_prefetch_e(P.wd + cta * 20736, 41472);
                    tm_prefetch_e(&tm_g); tm_prefetch_e(&tm_u); tm_prefetch_e(&tm_d); tm_prefetch_e(&tm_xs); tm_prefetch_e(&tm_o);
                } else if (it != 1 && it != 8) {
                    agent_job(G, &tm_g, &tm_u, warp, st, false);
                } else {
                    mbar_wait(BAR(B_INFO));
                    if (it == 8) {
                        mbar_arrive_e(BAR(B_QRD));
                        if (finish_o(o, accor, ow) || redo) redo = 1;
                        else { stage_o(SM_OHI, ow); PROXY_FENCE_SMEM(); mbar_arrive_e(BAR(B_OHA)); }
                        accor = 0;
                    }
                    float n0 = sq_h2(q[0]) + sq_h2(q[2]), n1 = sq_h2(q[1]) + sq_h2(q[3]);
                    if (t == 0) { n0 += sq_h2(q[4]); n1 += sq_h2(q[5]); }
                    n0 = ((t & 2) ? n1 : n0) + __shfl_xor_sync(~0u, (t & 2) ? n0 : n1, 2);
                    n0 += __shfl_xor_sync(~0u, n0, 1);
                    const float qn = __uint_as_float(__reduce_max_sync(~0u, __float_as_uint(n0))) * 262144.0f;
                    const float kp = ((const float*)(misc + MI_KP))[min(lane, 8)];
                    chk = __ballot_sync(~0u, !(qn * kp <= (lane < 8 ? 222.0f : 4096.0f) && qn <= 4096.0f));
                    if (chk & 0x100) redo |= it == 8 ? 2 : 1;
                    chk >>= it & 1;
                }
            }
            TSL(34 + it);
            if (chk & 1) {
                WG_WAIT(0);
#pragma unroll
                for (int i = 0; i < 64; i++) asm volatile("" : "+r"(s[i]) :: "memory");
#pragma unroll
                for (int i = 0; i < 64; i += 2) if ((i >> 1) & 3) accor |= s[i] | s[i + 1];
            }
            WG_WAIT(0);
#pragma unroll
            for (int i = 0; i < 64; i++) asm volatile("" : "+r"(s[i]) :: "memory");
            const uint64_t dv = mkdesc(sb + 256, 640, 128, 0) + (it & 7) * 1280;
#pragma unroll
            for (int h = 0; h < NSPLIT; h++) {
                constexpr int NR = 64 / NSPLIT;
#pragma unroll
                for (int i = h * NR; i < (h + 1) * NR; i++) s[i] = ((i >> 1) & 3) ? ex2_poly(s[i], cz, ca) : ex2_mufu(s[i]);
#pragma unroll
                for (int i = h * NR; i < (h + 1) * NR; i++) asm volatile("" : "+r"(s[i]) :: "memory");
                WG_FENCE();
#pragma unroll
                for (int c = h * NR / 4; c < (h + 1) * NR / 4; c++) {
                    if (c == 0) wgp_rs_n24_f32_f16(o, s[0], s[1], s[2], s[3], dv, it & 7);
                    else wg_rs_n24_f32_f16(o, s[4*c], s[4*c+1], s[4*c+2], s[4*c+3], dv + c * 80);
                }
            }
            WG_COMMIT();
            if (__builtin_expect((0x83 >> it) & 1, 0)) { if (it == 7) load_q(q, 4 + wg); else mbar_wait(BAR(B_KV1 + it)); }
            chk >>= 1; jobs >>= 1;
            const uint64_t dk = mkdesc(sb, 128, 640, 0) + ((it + 1) & 7) * 1280;
            WG_WAIT(0);
#pragma unroll
            for (int i = 0; i < 12; i++) asm volatile("" : "+f"(o[i]) :: "memory");
            if (it == 15) break;
            WG_FENCE();
            wgz_rs_n256_f16_f16(s, q[0], q[1], q[2], q[3], dk);
            wg_rs_n256_f16_f16(s, q[4], q[5], q[6], q[7], dk + 16);
            WG_COMMIT();
            if (it - 9u < 5u) mbar_arrive_e(BAR(B_KVD - 8 + it));
        }
        if (wq4 == 0) TS(18 + wg);
        tid = fresh_tid(); lane = tid & 31; g = lane >> 2; t = lane & 3;
        const int orow = wq4 * 16 + g;
        if (finish_o(o, accor, ow)) redo |= 2;
        if (redo) {
            uint32_t* res = G->tmp[cta][tid];
            if (redo & 1) {
                attn_safe(G, P.x, P.wq, qb * 64 + wq4 * 16, hg * 8 + wg, res);
                stage_o(SM_OHI, res); PROXY_FENCE_SMEM(); mbar_arrive_e(BAR(B_OHA));
            }
            if (redo & 2) {
                attn_safe(G, P.x, P.wq, qb * 64 + wq4 * 16, hg * 8 + 4 + wg, res);
#pragma unroll
                for (int i = 0; i < 6; i++) ow[i] = res[i];
            }
        }
#pragma unroll
        for (int i = 0; i < 6; i++) ow[i] = nz(ow[i]);
        const uint32_t tw = __shfl_sync(~0u, ow[1], lane | 3);
        mbar_wait(BAR(B_ZOK));
        uint8_t* go = (uint8_t*)G->ll.o[cta];
        const uint32_t oa1 = (2 * wg + (t >> 1)) * 1024 + orow * 16 + (t & 1) * 8;
        st_rlx8(go + oa1, ow[2], ow[4]); st_rlx8(go + oa1 + 128, ow[3], ow[5]);
        if (t >= 2) st_rlx4(go + 8192 + wg * 256 + (orow + (t == 2 ? 8 : 0)) * 4, t == 2 ? tw : ow[0]);
        if (wq4 == 0 && st != (0x6240 >> warp & 15)) agent_job(G, &tm_g, &tm_u, warp, st, true);
    }

    const int orow = wq4 * 16 + g;
    uint32_t wf[72];
    if (wg == 0) {
        float acc[72];
        mbar_arrive_e(BAR(B_END));
        mbar_wait(BAR(B_OHT));
        mbar_wait(BAR(B_OHA));
        TS(45); TSG(61);
        const uint4* const wo = G->wo + hg * 10368;
        uint64_t da = mkdesc(sb + SM_OHI, 1024, 128, 0);
#pragma unroll 1
        for (int p = 0; p < 6; p++) {
            if (p == 2) {
                WG_WAIT(0);
                mbar_arrive_e(BAR(B_G4));
                mbar_wait(BAR(B_END));
                TS(44);
                if (warp == 0) {
                    mbar_expect_e(BAR(B_WF + 2), 8 * 4608);
                    bulk_ld_e(sb, wo + 10 * 288, 8 * 4608, BAR(B_WF + 2));
                    mbar_wait(BAR(B_G4));
#pragma unroll 1
                    for (int u = 0; u < 3; u++) {
                        mbar_expect_e(BAR(B_WF + 3 + u), 6 * 4608);
                        bulk_ld_e(sb + (8 + 6 * u) * 4608, wo + (18 + 6 * u) * 288, 6 * 4608, BAR(B_WF + 3 + u));
                    }
                }
                stage_o(SM_OLO, ow);
                PROXY_FENCE_SMEM();
            }
            if (p == 3) {
                TS(3);
                BAR_SYNC(7, 512);
                TS(22);
                da = mkdesc(sb + SM_OLO, 1024, 128, 0);
            }
            uint64_t db = mkdesc(sb, 2304, 128, 0) + (p == 0 ? SM_A / 16 : (p == 1 ? SM_R / 16 : (p == 2 ? 0 : (6 * p - 10) * 288)));
            mbar_wait(BAR(B_WF + p));
            WG_FENCE();
#pragma unroll 1
            for (int u = (0x333432 >> (4 * p)) & 7; u > 0; u--) {
                wgp_ss_n144_f32_bf16(acc, da, db, p | (u ^ 2));
                wg_ss_n144_f32_bf16(acc, da + 128, db + 288);
                da += 256; db += 576;
            }
            WG_COMMIT();
            if (p == 3) { WG_WAIT(1); mbar_arrive_e(BAR(B_G8)); }
        }
        WG_WAIT(0);
        mbar_wait(BAR(B_XS));
#pragma unroll
        for (int i = 0; i < 72; i++) asm volatile("" : "+f"(acc[i]) :: "memory");
        TS(23);
        float sm[4] = {0, 0, 0, 0}, g1[4] = {0, 0, 0, 0}, g2[4] = {0, 0, 0, 0}, g3[4] = {0, 0, 0, 0}, g4[4] = {0, 0, 0, 0};
        const uint32_t xaddr = sb + SM_XS + (wq4 * 16 + (lane & 15)) * 304 + (lane >> 4) * 16;
        const uint8_t* wr = smem + (g == 1 ? SM_XS + 64 * 304 : SM_MISC + MI_ONE) + t * 4;
#pragma unroll
        for (int s = 0; s < 9; s++) {
            uint32_t hw[4];
            ldsm4(hw, xaddr + s * 32);
            const uint32_t w0 = *(const uint32_t*)(wr + s * 32), w1 = *(const uint32_t*)(wr + s * 32 + 16);
#pragma unroll
            for (int i = 0; i < 4; i++) hw[i] = add_bf2(hw[i], pk_bf(acc[8*s+2*i], acc[8*s+2*i+1]));
            mma_bf16(sm, hw[0], hw[1], hw[2], hw[3], w0, w1);
            mma_bf16_k8(g1, hw[0], hw[1], hw[0]); mma_bf16_k8(g2, hw[0], hw[1], hw[1]);
            mma_bf16_k8(g3, hw[2], hw[3], hw[2]); mma_bf16_k8(g4, hw[2], hw[3], hw[3]);
            stsm4(xaddr + s * 32, hw[0], hw[1], hw[2], hw[3]);
        }
        const int dl = (lane & 28) | (g >> 1);
        const float q0 = __shfl_sync(~0u, (g & 1) ? g1[1] + g3[1] : g1[0] + g3[0], dl), q1 = __shfl_sync(~0u, (g & 1) ? g2[3] + g4[3] : g2[2] + g4[2], dl);
        float4* part = G->ll.part[qb][hg] + orow;
        if (t == 0) {
            st_rlx16(part, nzf(sm[0]), nzf(q0), nzf(sm[1]), 1u);
            st_rlx16(part + 8, nzf(sm[2]), nzf(q1), nzf(sm[3]), 1u);
        }
        TS(4);
        __syncwarp();
        delay(DLY1);
        const float4* pin = G->ll.part[qb][t] + orow;
        uint4 pp[2];
        ll_load(2, 8, pp, (const uint4*)pin);
        const uint4 p0 = pp[0], p1 = pp[1];
        TS(46);
        const bool up = t & 2;
        float v0 = __uint_as_float(up ? p1.x : p0.x) + __shfl_xor_sync(~0u, __uint_as_float(up ? p0.x : p1.x), 2);
        float v1 = __uint_as_float(up ? p1.y : p0.y) + __shfl_xor_sync(~0u, __uint_as_float(up ? p0.y : p1.y), 2);
        float v2 = __uint_as_float(up ? p1.z : p0.z) + __shfl_xor_sync(~0u, __uint_as_float(up ? p0.z : p1.z), 2);
        v0 += __shfl_xor_sync(~0u, v0, 1); v1 += __shfl_xor_sync(~0u, v1, 1); v2 += __shfl_xor_sync(~0u, v2, 1);
        const float2 st = ln_stats(v0, v1);
        uint32_t u = __float_as_uint((v2 - st.x * *(const float*)(smem + SM_SW)) * st.y);
        u ^= ((int)u >> 31) | 0x80000000u;
        const int lr = orow + (t & 2) * 4;
        ((uint32_t*)(misc + MI_CS))[lr] = nz((u & 0xFFFFF800u) | (2047 - (qb * 64 + lr)));
        ((float2*)(misc + MI_STAT))[lr] = st;
        TS(24);
    } else {
        mbar_wait(BAR(B_GU));
        {
            const int mat = lane >> 3;
            const uint32_t wa = sb + wq4 * 23040 + (mat & 1) * 11520 + ((mat >> 1) * 8 + (lane & 7)) * 80 + (wg - 1) * 32;
#pragma unroll
            for (int s = 0; s < 9; s++) { ldsm4t(wf + 8 * s, wa + s * 1280); ldsm4t(wf + 8 * s + 4, wa + s * 1280 + 16); }
        }
        mbar_arrive_e(BAR(B_END));
        mbar_wait(BAR(B_END));
        stage_o(SM_OLO, ow);
        if (DLYO) delay(DLYO);
        const int tl = tid & 127;
        const uint4* src = (const uint4*)G->ll.o[4 * qb + ((hg + wg) & 3)] + tl;
        uint4 v[5];
        uint8_t* so = smem + SM_OLO + wg * 9216;
        if (wq4 < 2) {
            ll_load(5, 128, v, src);
            uint32_t* d = (uint32_t*)(so + 8192 + (tl & 15) * 64 + (tl >> 4) * 4);
            d[0] = v[4].x; d[4] = v[4].y; d[8] = v[4].z; d[12] = v[4].w;
        } else ll_load(4, 128, v, src);
#pragma unroll
        for (int j = 0; j < 4; j++) ((uint4*)so)[tl + j * 128] = v[j];
        if (warp == 7) {
            ((uint4*)(misc + MI_ONE))[lane] = make_uint4(ONE2, ONE2, ONE2, ONE2);
            ((uint4*)(misc + MI_ACT))[lane] = make_uint4(0, 0, 0, 0); ((uint4*)(misc + MI_ACT + 384))[lane] = make_uint4(0, 0, 0, 0);
        }
        PROXY_FENCE_SMEM();
        BAR_ARRIVE(7, 512);
        if (warp == 4) {
            mbar_wait(BAR(B_G8));
            mbar_expect_e(BAR(B_XS), 64 * 304 + 288);
            tma2d_e(sb + SM_XS, &tm_xs, hg * 144, qb * 64, BAR(B_XS));
            bulk_ld_e(sb + SM_XS + 64 * 304, P.wr + hg * 144, 288, BAR(B_XS));
            mbar_expect_e(BAR(B_DN), 3 * 14400);
            tma2d_e(sb + SM_DN0, &tm_d, 0, cta * 36, BAR(B_DN));
            tma2d_e(sb + SM_DN1, &tm_d, 192, cta * 36, BAR(B_DN));
            tma2d_e(sb + SM_DN2, &tm_d, 384, cta * 36, BAR(B_DN));
        }
    }
    BAR_SYNC(10, 512);

    {
        const uint32_t* keys = (const uint32_t*)(misc + MI_CS);
        const uint32_t ka = keys[lane], kb = keys[lane + 32];
        const uint4 mk = ((const uint4*)keys)[warp];
        const uint32_t my[4] = {mk.x, mk.y, mk.z, mk.w};
        uint32_t rk = 0;
#pragma unroll
        for (int i = 0; i < 4; i++) {
            const uint32_t r = __popc(__ballot_sync(~0u, ka > my[i])) + __popc(__ballot_sync(~0u, kb > my[i]));
            if (r < 8) ((uint32_t*)(misc + MI_TOP))[r] = my[i];
            rk |= r << (8 * i);
        }
        if (warp < 2) {
            BAR_SYNC(12, 512);
            const uint4 v = ((const uint4*)(misc + MI_TOP))[tid & 1];
            st_rlx16(&G->ll.top[hg * 32 + (tid >> 1)][2 * qb + (tid & 1)], v.x, v.y, v.z, v.w);
            if (warp == 0) TS(49);
        } else BAR_ARRIVE(12, 512);
#pragma unroll 1
        for (int i = 0; i < 4; i++, rk >>= 8) {
            if ((rk & 0xF8) == 0 && lane < 18) {
                const int r = 4 * warp + i;
                const uint4 v = *(const uint4*)(smem + SM_XS + r * 304 + lane * 16);
                const float2 st = ((const float2*)(misc + MI_STAT))[r];
                const uint32_t m2 = (__float_as_uint(st.x) >> 16) * 0x10001u;
                uint32_t* pn = G->ll.hn[qb][rk & 7] + hg * 72 + lane * 4;
                st_rlx16(pn, nz(ln_apply(v.x, m2, st.y)), nz(ln_apply(v.y, m2, st.y)), nz(ln_apply(v.z, m2, st.y)), nz(ln_apply(v.w, m2, st.y)));
                st_rlx16(pn + 32 * 8 * 288, nz(v.x), nz(v.y), nz(v.z), nz(v.w));
            }
        }
        __syncwarp();
    }
    uint32_t hsw = 0;
    float sgm = 0.f;
    bf16* outp = nullptr;
    if (wg == 0) {
#pragma unroll 3
        for (int it = 0; it < 9; it++) {
            const int i = it * 32 + lane, r = wq4 * 16 + i / 18, c = i % 18;
            const uint4 v = *(const uint4*)(smem + SM_XS + r * 304 + c * 16);
            const float2 st = ((const float2*)(misc + MI_STAT))[r];
            const uint32_t m2 = (__float_as_uint(st.x) >> 16) * 0x10001u;
            *(uint4*)(smem + SM_OUT + wq4 * 4608 + i * 16) = make_uint4(add_bf2(v.x, ln_apply(v.x, m2, st.y)), add_bf2(v.y, ln_apply(v.y, m2, st.y)),
                                                                       add_bf2(v.z, ln_apply(v.z, m2, st.y)), add_bf2(v.w, ln_apply(v.w, m2, st.y)));
        }
        PROXY_FENCE_SMEM();
        TS(5);
        BAR_SYNC(11, 512);
        tma2d_st_e(&tm_o, hg * 144, qb * 64 + wq4 * 16, sb + SM_OUT + wq4 * 4608);
        asm volatile("cp.async.bulk.commit_group;\ncp.async.bulk.wait_group 0;" ::: "memory");
        PROXY_FENCE_GMEM();
        TS(6);
        BAR_SYNC(9, 512);
    } else {
        if (wg > 1) {
            const int w8 = warp - 8;
            delay(DLY2);
            const uint4* ks = G->ll.top[cta] + 2 * lane;
            uint4 ab[2];
            ll_load(2, 1, ab, ks);
            uint4 a = ab[0], b = ab[1];
            if (w8 == 7) TS(25);
            uint32_t pops = 0, key = __reduce_max_sync(~0u, a.x);
#pragma unroll 1
            for (int r = 0; r < w8; r++) {
                if (a.x == key) { a.x = a.y; a.y = a.z; a.z = a.w; a.w = b.x; b.x = b.y; b.y = b.z; b.z = b.w; pops++; }
                key = __reduce_max_sync(~0u, a.x);
            }
            const int tok = 2047 - (key & 2047);
            const uint32_t slot = __shfl_sync(~0u, pops, tok >> 6);
            if (w8 == 7) TS(47);
            uint4 hv[3];
            ll_load(3, 24, hv, (const uint4*)G->ll.hn[tok >> 6][slot] + min(lane, 23));
            uint4* hd = (uint4*)(smem + SM_HN + w8 * 1168) + min(lane, 23);
            hd[0] = hv[0]; hd[24] = hv[1]; hd[48] = hv[2];
            ((uint2*)(misc + MI_SEL))[w8] = make_uint2(key, slot);
        }
        BAR_SYNC(11, OUT_LATE ? 512 : 384);
        if (warp == 4) TS(26);

        const int w12 = warp - 4;
        {
            uint32_t b[20];
#pragma unroll
            for (int i = 0; i < 5; i++) ldsm4(b + 4 * i, sb + SM_HN + (lane & 7) * 1168 + wq4 * 288 + (lane >> 3) * 16 + i * 64);
            float c[4][4];
#pragma unroll
            for (int i = 0; i < 16; i++) c[i >> 2][i & 3] = 0.f;
#pragma unroll
            for (int s = 0; s < 9; s++) {
                mma_bf16(c[s & 1], wf[8*s], wf[8*s+1], wf[8*s+2], wf[8*s+3], b[2*s], b[2*s+1]);
                mma_bf16(c[2 + (s & 1)], wf[8*s+4], wf[8*s+5], wf[8*s+6], wf[8*s+7], b[2*s], b[2*s+1]);
            }
            float4* red = (float4*)(smem + SM_RED) + wq4 * 160 + (wg - 1) * 64 + lane;
            red[0] = make_float4(c[0][0] + c[1][0], c[0][1] + c[1][1], c[0][2] + c[1][2], c[0][3] + c[1][3]);
            if (wg < 3) red[32] = make_float4(c[2][0] + c[3][0], c[2][1] + c[3][1], c[2][2] + c[3][2], c[2][3] + c[3][3]);
        }
        if (warp == 4) TS(27);
        BAR_SYNC(13, 384);
        if (w12 < 5) {
            const float4* red = (const float4*)(smem + SM_RED) + w12 * 32 + lane;
            const float4 a = red[0], b = red[160], c = red[320], d = red[480];
            const float g0 = bfr((a.x + b.x) + (c.x + d.x)), g1 = bfr((a.y + b.y) + (c.y + d.y));
            const float u0 = bfr((a.z + b.z) + (c.z + d.z)), u1 = bfr((a.w + b.w) + (c.w + d.w));
            const float y0 = bfr(g0 * frcp(1.0f + __expf(-g0))) * u0, y1 = bfr(g1 * frcp(1.0f + __expf(-g1))) * u1;
            const int f = 8 * w12 + g - (cta & 1) * 4;
            if (f >= 0 && f < 36) {
                bf16* act = (bf16*)(misc + MI_ACT);
                act[(2 * t) * 56 + f] = __float2bfloat16_rn(y0);
                act[(2 * t + 1) * 56 + f] = __float2bfloat16_rn(y1);
            }
        }
        mbar_wait(BAR(B_DN));
        {
            const int mat = lane >> 3, r = lane & 7;
#pragma unroll
            for (int i = 0; i < 9; i++)
                ldsm4t(wf + 4 * i, sb + (i < 3 ? SM_DN0 : (i < 6 ? SM_DN1 : SM_DN2)) + min(16 * (i % 3) + (mat >> 1) * 8 + r, 35) * 400 + (16 * w12 + (mat & 1) * 8) * 2);
        }
        if (warp == 4) TS(48);
        BAR_SYNC(9, 512);
        if (warp == 4) TS(28);
        {
            uint32_t b[6];
#pragma unroll
            for (int i = 0; i < 6; i++) b[i] = *(const uint32_t*)(misc + MI_ACT + g * 112 + i * 16 + t * 4);
            float c[3][4];
#pragma unroll
            for (int i = 0; i < 12; i++) c[i >> 2][i & 3] = 0.f;
#pragma unroll
            for (int i = 0; i < 9; i++) { const int it = i % 3, s = i / 3, j = 12 * it + 4 * s; mma_bf16(c[it], wf[j], wf[j+1], wf[j+2], wf[j+3], b[2*s], b[2*s+1]); }
#pragma unroll
            for (int it = 0; it < 3; it++) {
                uint32_t* yp = &G->ll.y[2 * (w12 + 12 * it)][cta][lane];
                st_rlx4(yp, nz(pk_bf(c[it][0], c[it][1])));
                st_rlx4(yp + NCTA * 32, nz(pk_bf(c[it][2], c[it][3])));
            }
        }
        if (warp == 4) TS(29);
        if (warp < 6 && cta < 72) {
            const int e = tid & 63;
            const uint2 sel = ((const uint2*)(misc + MI_SEL))[e & 7];
            const uint32_t* hp = G->ll.hs[(2047 - (sel.x & 2047)) >> 6][sel.y] + cta * 4 + (e >> 4);
            hsw = ld_rlx4(hp);
            uint32_t u = (sel.x & 0xFFFFF800u) | 0x400u;
            u ^= (~(int)u >> 31) | 0x80000000u;
            sgm = bfr(frcp(1.0f + __expf(-bfr(__uint_as_float(u)))));
            outp = P.out + (2047 - (sel.x & 2047)) * DM + cta * 8 + (e >> 3);
            ll_fix4(hsw, hp);
            const uint32_t hnw = ((const uint32_t*)(smem + SM_HN + (e & 7) * 1168))[cta * 4 + (e >> 4)];
            hsw = (e & 8) ? __byte_perm(hsw, hnw, 0x7632) : __byte_perm(hsw, hnw, 0x5410);
        }
    }
    if (cta < 72) {
        if (warp < 4 || warp > 5) delay(warp < 4 ? DLY3 + 250 : DLY3);
        const uint4* src = (const uint4*)G->ll.y[cta] + tid;
        uint4 vv[2];
        ll_load(2, 512, vv, src);
        const uint4 va = vv[0], vb = vv[1];
        float s[8] = {bf_lo(va.x) + bf_lo(vb.x), bf_hi(va.x) + bf_hi(vb.x), bf_lo(va.y) + bf_lo(vb.y), bf_hi(va.y) + bf_hi(vb.y),
                      bf_lo(va.z) + bf_lo(vb.z), bf_hi(va.z) + bf_hi(vb.z), bf_lo(va.w) + bf_lo(vb.w), bf_hi(va.w) + bf_hi(vb.w)};
        const bool u4 = lane & 16, u2 = lane & 8;
#pragma unroll
        for (int i = 0; i < 4; i++) s[i] = (u4 ? s[i + 4] : s[i]) + __shfl_xor_sync(~0u, u4 ? s[i] : s[i + 4], 16);
#pragma unroll
        for (int i = 0; i < 2; i++) s[i] = (u2 ? s[i + 2] : s[i]) + __shfl_xor_sync(~0u, u2 ? s[i] : s[i + 2], 8);
        *(float2*)(misc + MI_Z + warp * 256 + (lane & 7) * 32 + (lane >> 3) * 8) = make_float2(s[0], s[1]);
        BAR_SYNC(8, 512);
        if (warp == 4) TS(30);
        if (warp == 4 || warp == 5) {
            const int e = tid & 63;
            float y = 0.f;
#pragma unroll
            for (int w = 0; w < 16; w++) y += ((const float*)(misc + MI_Z))[w * 64 + e];
            *outp = __float2bfloat16_rn(bf_lo(hsw) + bfr(bf_hi(hsw) + bfr(bfr(y) * sgm)));
        }
        if (cta == 0 && tid == 0) { G->cnt[0] = 0; G->cnt[32] = 0; }
    }
    if (warp == 4) { TS(31); TSG(33); }
    MARK(99999);
}

typedef CUresult (*EncodeFn)(CUtensorMap*, CUtensorMapDataType, cuuint32_t, void*, const cuuint64_t*, const cuuint64_t*,
                             const cuuint32_t*, const cuuint32_t*, CUtensorMapInterleave, CUtensorMapSwizzle,
                             CUtensorMapL2promotion, CUtensorMapFloatOOBfill);

static void make_map(EncodeFn enc, CUtensorMap* tm, const void* p, int cols, int rows, int bc, int br, CUtensorMapSwizzle sw) {
    cuuint64_t gd[2] = {(cuuint64_t)cols, (cuuint64_t)rows}, gs[1] = {(cuuint64_t)cols * 2};
    cuuint32_t bx[2] = {(cuuint32_t)bc, (cuuint32_t)br}, es[2] = {1, 1};
    enc(tm, CU_TENSOR_MAP_DATA_TYPE_BFLOAT16, 2, (void*)p, gd, gs, bx, es, CU_TENSOR_MAP_INTERLEAVE_NONE, sw,
        CU_TENSOR_MAP_L2_PROMOTION_L2_128B, CU_TENSOR_MAP_FLOAT_OOB_FILL_NONE);
}

extern "C" void kernel_launch(void* const* d_in, const int* in_sizes, int n_in, void* d_out, int out_size) {
    static EncodeFn enc = nullptr;
    static void* scratch = nullptr;
    if (!enc) {
        void* fn = nullptr;
        cudaDriverEntryPointQueryResult qr;
        cudaGetDriverEntryPoint("cuTensorMapEncodeTiled", &fn, cudaEnableDefault, &qr);
        enc = (EncodeFn)fn;
        cudaGetSymbolAddress(&scratch, g_scratch);
        cudaFuncSetAttribute(fused_block, cudaFuncAttributeMaxDynamicSharedMemorySize, SM_TOTAL);
    }
    Params P;
    P.g = (Scratch*)scratch;
    P.x = (const bf16*)d_in[0]; P.wq = (const bf16*)d_in[1]; P.wk = (const bf16*)d_in[2]; P.wv = (const bf16*)d_in[3];
    P.wo = (const bf16*)d_in[4]; P.wr = (const bf16*)d_in[6]; P.wg = (const bf16*)d_in[7]; P.wu = (const bf16*)d_in[8];
    P.wd = (const bf16*)d_in[9]; P.out = (bf16*)d_out;
    CUtensorMap tx, twq, twqt, tg, tu, txs, td, to;
    make_map(enc, &tx, P.x, DM, SEQ, 64, 64, CU_TENSOR_MAP_SWIZZLE_128B);
    make_map(enc, &twq, P.wq, DM, DM, 64, 64, CU_TENSOR_MAP_SWIZZLE_128B);
    make_map(enc, &twqt, P.wq, DM, DM, 16, 64, CU_TENSOR_MAP_SWIZZLE_32B);
    make_map(enc, &tg, P.wg, FF, DM, 40, 144, CU_TENSOR_MAP_SWIZZLE_NONE);
    make_map(enc, &tu, P.wu, FF, DM, 40, 144, CU_TENSOR_MAP_SWIZZLE_NONE);
    make_map(enc, &txs, P.x, DM, SEQ, 152, 64, CU_TENSOR_MAP_SWIZZLE_NONE);
    make_map(enc, &td, P.wd, DM, FF, 200, 36, CU_TENSOR_MAP_SWIZZLE_NONE);
    make_map(enc, &to, P.out, DM, SEQ, 144, 16, CU_TENSOR_MAP_SWIZZLE_NONE);
    fused_block<<<NCTA, NTHR, SM_TOTAL, cudaStreamPerThread>>>(P, tx, twq, twqt, tg, tu, txs, td, to);
}
```

```cpp
#include <cuda_runtime.h>
#include <cuda_bf16.h>
#include <cuda_fp16.h>
#include <cuda.h>
#include <stdint.h>

#define POLY_DEG3 0

__device__ __forceinline__ void wgz_rs_n256_f16_f16(uint32_t* d, uint32_t a0, uint32_t a1, uint32_t a2, uint32_t a3, uint64_t db) {
  asm volatile("{\n.reg .pred p;\nsetp.ne.b32 p, 0, 0;\n"
    "wgmma.mma_async.sync.aligned.m64n256k16.f16.f16.f16 "
    "{%0,%1,%2,%3,%4,%5,%6,%7,%8,%9,%10,%11,%12,%13,%14,%15,%16,%17,%18,%19,%20,%21,%22,%23,%24,%25,%26,%27,%28,%29,%30,%31,%32,%33,%34,%35,%36,%37,%38,%39,%40,%41,%42,%43,%44,%45,%46,%47,%48,%49,%50,%51,%52,%53,%54,%55,%56,%57,%58,%59,%60,%61,%62,%63}, "
    "{%64,%65,%66,%67}, %68, p, 1, 1, 0;\n}\n"
    : "=r"(d[0]), "=r"(d[1]), "=r"(d[2]), "=r"(d[3]), "=r"(d[4]), "=r"(d[5]), "=r"(d[6]), "=r"(d[7]),
      "=r"(d[8]), "=r"(d[9]), "=r"(d[10]), "=r"(d[11]), "=r"(d[12]), "=r"(d[13]), "=r"(d[14]), "=r"(d[15]),
      "=r"(d[16]), "=r"(d[17]), "=r"(d[18]), "=r"(d[19]), "=r"(d[20]), "=r"(d[21]), "=r"(d[22]), "=r"(d[23]),
      "=r"(d[24]), "=r"(d[25]), "=r"(d[26]), "=r"(d[27]), "=r"(d[28]), "=r"(d[29]), "=r"(d[30]), "=r"(d[31]),
      "=r"(d[32]), "=r"(d[33]), "=r"(d[34]), "=r"(d[35]), "=r"(d[36]), "=r"(d[37]), "=r"(d[38]), "=r"(d[39]),
      "=r"(d[40]), "=r"(d[41]), "=r"(d[42]), "=r"(d[43]), "=r"(d[44]), "=r"(d[45]), "=r"(d[46]), "=r"(d[47]),
      "=r"(d[48]), "=r"(d[49]), "=r"(d[50]), "=r"(d[51]), "=r"(d[52]), "=r"(d[53]), "=r"(d[54]), "=r"(d[55]),
      "=r"(d[56]), "=r"(d[57]), "=r"(d[58]), "=r"(d[59]), "=r"(d[60]), "=r"(d[61]), "=r"(d[62]), "=r"(d[63])
    : "r"(a0), "r"(a1), "r"(a2), "r"(a3), "l"(db));
}
__device__ __forceinline__ void wg_rs_n256_f16_f16(uint32_t* d, uint32_t a0, uint32_t a1, uint32_t a2, uint32_t a3, uint64_t db) {
  asm volatile("{\n.reg .pred p;\nsetp.ne.b32 p, 1, 0;\n"
    "wgmma.mma_async.sync.aligned.m64n256k16.f16.f16.f16 "
    "{%0,%1,%2,%3,%4,%5,%6,%7,%8,%9,%10,%11,%12,%13,%14,%15,%16,%17,%18,%19,%20,%21,%22,%23,%24,%25,%26,%27,%28,%29,%30,%31,%32,%33,%34,%35,%36,%37,%38,%39,%40,%41,%42,%43,%44,%45,%46,%47,%48,%49,%50,%51,%52,%53,%54,%55,%56,%57,%58,%59,%60,%61,%62,%63}, "
    "{%64,%65,%66,%67}, %68, p, 1, 1, 0;\n}\n"
    : "+r"(d[0]), "+r"(d[1]), "+r"(d[2]), "+r"(d[3]), "+r"(d[4]), "+r"(d[5]), "+r"(d[6]), "+r"(d[7]),
      "+r"(d[8]), "+r"(d[9]), "+r"(d[10]), "+r"(d[11]), "+r"(d[12]), "+r"(d[13]), "+r"(d[14]), "+r"(d[15]),
      "+r"(d[16]), "+r"(d[17]), "+r"(d[18]), "+r"(d[19]), "+r"(d[20]), "+r"(d[21]), "+r"(d[22]), "+r"(d[23]),
      "+r"(d[24]), "+r"(d[25]), "+r"(d[26]), "+r"(d[27]), "+r"(d[28]), "+r"(d[29]), "+r"(d[30]), "+r"(d[31]),
      "+r"(d[32]), "+r"(d[33]), "+r"(d[34]), "+r"(d[35]), "+r"(d[36]), "+r"(d[37]), "+r"(d[38]), "+r"(d[39]),
      "+r"(d[40]), "+r"(d[41]), "+r"(d[42]), "+r"(d[43]), "+r"(d[44]), "+r"(d[45]), "+r"(d[46]), "+r"(d[47]),
      "+r"(d[48]), "+r"(d[49]), "+r"(d[50]), "+r"(d[51]), "+r"(d[52]), "+r"(d[53]), "+r"(d[54]), "+r"(d[55]),
      "+r"(d[56]), "+r"(d[57]), "+r"(d[58]), "+r"(d[59]), "+r"(d[60]), "+r"(d[61]), "+r"(d[62]), "+r"(d[63])
    : "r"(a0), "r"(a1), "r"(a2), "r"(a3), "l"(db));
}
__device__ __forceinline__ void wg_rs_n24_f32_f16(float* d, uint32_t a0, uint32_t a1, uint32_t a2, uint32_t a3, uint64_t db) {
  asm volatile("{\n.reg .pred p;\nsetp.ne.b32 p, 1, 0;\n"
    "wgmma.mma_async.sync.aligned.m64n24k16.f32.f16.f16 "
    "{%0,%1,%2,%3,%4,%5,%6,%7,%8,%9,%10,%11}, "
    "{%12,%13,%14,%15}, %16, p, 1, 1, 1;\n}\n"
    : "+f"(d[0]), "+f"(d[1]), "+f"(d[2]), "+f"(d[3]), "+f"(d[4]), "+f"(d[5]), "+f"(d[6]), "+f"(d[7]),
      "+f"(d[8]), "+f"(d[9]), "+f"(d[10]), "+f"(d[11])
    : "r"(a0), "r"(a1), "r"(a2), "r"(a3), "l"(db));
}
__device__ __forceinline__ void wgp_rs_n24_f32_f16(float* d, uint32_t a0, uint32_t a1, uint32_t a2, uint32_t a3, uint64_t db, uint32_t sd) {
  asm volatile("{\n.reg .pred p;\nsetp.ne.b32 p, %17, 0;\n"
    "wgmma.mma_async.sync.aligned.m64n24k16.f32.f16.f16 "
    "{%0,%1,%2,%3,%4,%5,%6,%7,%8,%9,%10,%11}, "
    "{%12,%13,%14,%15}, %16, p, 1, 1, 1;\n}\n"
    : "+f"(d[0]), "+f"(d[1]), "+f"(d[2]), "+f"(d[3]), "+f"(d[4]), "+f"(d[5]), "+f"(d[6]), "+f"(d[7]),
      "+f"(d[8]), "+f"(d[9]), "+f"(d[10]), "+f"(d[11])
    : "r"(a0), "r"(a1), "r"(a2), "r"(a3), "l"(db), "r"(sd));
}
__device__ __forceinline__ void wgp_ss_n128_f32_bf16(float* d, uint64_t da, uint64_t db, uint32_t sd) {
  asm volatile("{\n.reg .pred p;\nsetp.ne.b32 p, %66, 0;\n"
    "wgmma.mma_async.sync.aligned.m64n128k16.f32.bf16.bf16 "
    "{%0,%1,%2,%3,%4,%5,%6,%7,%8,%9,%10,%11,%12,%13,%14,%15,%16,%17,%18,%19,%20,%21,%22,%23,%24,%25,%26,%27,%28,%29,%30,%31,%32,%33,%34,%35,%36,%37,%38,%39,%40,%41,%42,%43,%44,%45,%46,%47,%48,%49,%50,%51,%52,%53,%54,%55,%56,%57,%58,%59,%60,%61,%62,%63}, "
    "%64, %65, p, 1, 1, 0, 1;\n}\n"
    : "+f"(d[0]), "+f"(d[1]), "+f"(d[2]), "+f"(d[3]), "+f"(d[4]), "+f"(d[5]), "+f"(d[6]), "+f"(d[7]),
      "+f"(d[8]), "+f"(d[9]), "+f"(d[10]), "+f"(d[11]), "+f"(d[12]), "+f"(d[13]), "+f"(d[14]), "+f"(d[15]),
      "+f"(d[16]), "+f"(d[17]), "+f"(d[18]), "+f"(d[19]), "+f"(d[20]), "+f"(d[21]), "+f"(d[22]), "+f"(d[23]),
      "+f"(d[24]), "+f"(d[25]), "+f"(d[26]), "+f"(d[27]), "+f"(d[28]), "+f"(d[29]), "+f"(d[30]), "+f"(d[31]),
      "+f"(d[32]), "+f"(d[33]), "+f"(d[34]), "+f"(d[35]), "+f"(d[36]), "+f"(d[37]), "+f"(d[38]), "+f"(d[39]),
      "+f"(d[40]), "+f"(d[41]), "+f"(d[42]), "+f"(d[43]), "+f"(d[44]), "+f"(d[45]), "+f"(d[46]), "+f"(d[47]),
      "+f"(d[48]), "+f"(d[49]), "+f"(d[50]), "+f"(d[51]), "+f"(d[52]), "+f"(d[53]), "+f"(d[54]), "+f"(d[55]),
      "+f"(d[56]), "+f"(d[57]), "+f"(d[58]), "+f"(d[59]), "+f"(d[60]), "+f"(d[61]), "+f"(d[62]), "+f"(d[63])
    : "l"(da), "l"(db), "r"(sd));
}
__device__ __forceinline__ void wg_ss_n128_f32_bf16(float* d, uint64_t da, uint64_t db) {
  asm volatile("{\n.reg .pred p;\nsetp.ne.b32 p, 1, 0;\n"
    "wgmma.mma_async.sync.aligned.m64n128k16.f32.bf16.bf16 "
    "{%0,%1,%2,%3,%4,%5,%6,%7,%8,%9,%10,%11,%12,%13,%14,%15,%16,%17,%18,%19,%20,%21,%22,%23,%24,%25,%26,%27,%28,%29,%30,%31,%32,%33,%34,%35,%36,%37,%38,%39,%40,%41,%42,%43,%44,%45,%46,%47,%48,%49,%50,%51,%52,%53,%54,%55,%56,%57,%58,%59,%60,%61,%62,%63}, "
    "%64, %65, p, 1, 1, 0, 1;\n}\n"
    : "+f"(d[0]), "+f"(d[1]), "+f"(d[2]), "+f"(d[3]), "+f"(d[4]), "+f"(d[5]), "+f"(d[6]), "+f"(d[7]),
      "+f"(d[8]), "+f"(d[9]), "+f"(d[10]), "+f"(d[11]), "+f"(d[12]), "+f"(d[13]), "+f"(d[14]), "+f"(d[15]),
      "+f"(d[16]), "+f"(d[17]), "+f"(d[18]), "+f"(d[19]), "+f"(d[20]), "+f"(d[21]), "+f"(d[22]), "+f"(d[23]),
      "+f"(d[24]), "+f"(d[25]), "+f"(d[26]), "+f"(d[27]), "+f"(d[28]), "+f"(d[29]), "+f"(d[30]), "+f"(d[31]),
      "+f"(d[32]), "+f"(d[33]), "+f"(d[34]), "+f"(d[35]), "+f"(d[36]), "+f"(d[37]), "+f"(d[38]), "+f"(d[39]),
      "+f"(d[40]), "+f"(d[41]), "+f"(d[42]), "+f"(d[43]), "+f"(d[44]), "+f"(d[45]), "+f"(d[46]), "+f"(d[47]),
      "+f"(d[48]), "+f"(d[49]), "+f"(d[50]), "+f"(d[51]), "+f"(d[52]), "+f"(d[53]), "+f"(d[54]), "+f"(d[55]),
      "+f"(d[56]), "+f"(d[57]), "+f"(d[58]), "+f"(d[59]), "+f"(d[60]), "+f"(d[61]), "+f"(d[62]), "+f"(d[63])
    : "l"(da), "l"(db));
}
__device__ __forceinline__ void wgp_ss_n32_f32_bf16(float* d, uint64_t da, uint64_t db, uint32_t sd) {
  asm volatile("{\n.reg .pred p;\nsetp.ne.b32 p, %18, 0;\n"
    "wgmma.mma_async.sync.aligned.m64n32k16.f32.bf16.bf16 "
    "{%0,%1,%2,%3,%4,%5,%6,%7,%8,%9,%10,%11,%12,%13,%14,%15}, "
    "%16, %17, p, 1, 1, 0, 1;\n}\n"
    : "+f"(d[0]), "+f"(d[1]), "+f"(d[2]), "+f"(d[3]), "+f"(d[4]), "+f"(d[5]), "+f"(d[6]), "+f"(d[7]),
      "+f"(d[8]), "+f"(d[9]), "+f"(d[10]), "+f"(d[11]), "+f"(d[12]), "+f"(d[13]), "+f"(d[14]), "+f"(d[15])
    : "l"(da), "l"(db), "r"(sd));
}
__device__ __forceinline__ void wg_ss_n32_f32_bf16(float* d, uint64_t da, uint64_t db) {
  asm volatile("{\n.reg .pred p;\nsetp.ne.b32 p, 1, 0;\n"
    "wgmma.mma_async.sync.aligned.m64n32k16.f32.bf16.bf16 "
    "{%0,%1,%2,%3,%4,%5,%6,%7,%8,%9,%10,%11,%12,%13,%14,%15}, "
    "%16, %17, p, 1, 1, 0, 1;\n}\n"
    : "+f"(d[0]), "+f"(d[1]), "+f"(d[2]), "+f"(d[3]), "+f"(d[4]), "+f"(d[5]), "+f"(d[6]), "+f"(d[7]),
      "+f"(d[8]), "+f"(d[9]), "+f"(d[10]), "+f"(d[11]), "+f"(d[12]), "+f"(d[13]), "+f"(d[14]), "+f"(d[15])
    : "l"(da), "l"(db));
}
__device__ __forceinline__ void wg_rs_n128_f32_bf16(float* d, uint32_t a0, uint32_t a1, uint32_t a2, uint32_t a3, uint64_t db) {
  asm volatile("{\n.reg .pred p;\nsetp.ne.b32 p, 1, 0;\n"
    "wgmma.mma_async.sync.aligned.m64n128k16.f32.bf16.bf16 "
    "{%0,%1,%2,%3,%4,%5,%6,%7,%8,%9,%10,%11,%12,%13,%14,%15,%16,%17,%18,%19,%20,%21,%22,%23,%24,%25,%26,%27,%28,%29,%30,%31,%32,%33,%34,%35,%36,%37,%38,%39,%40,%41,%42,%43,%44,%45,%46,%47,%48,%49,%50,%51,%52,%53,%54,%55,%56,%57,%58,%59,%60,%61,%62,%63}, "
    "{%64,%65,%66,%67}, %68, p, 1, 1, 1;\n}\n"
    : "+f"(d[0]), "+f"(d[1]), "+f"(d[2]), "+f"(d[3]), "+f"(d[4]), "+f"(d[5]), "+f"(d[6]), "+f"(d[7]),
      "+f"(d[8]), "+f"(d[9]), "+f"(d[10]), "+f"(d[11]), "+f"(d[12]), "+f"(d[13]), "+f"(d[14]), "+f"(d[15]),
      "+f"(d[16]), "+f"(d[17]), "+f"(d[18]), "+f"(d[19]), "+f"(d[20]), "+f"(d[21]), "+f"(d[22]), "+f"(d[23]),
      "+f"(d[24]), "+f"(d[25]), "+f"(d[26]), "+f"(d[27]), "+f"(d[28]), "+f"(d[29]), "+f"(d[30]), "+f"(d[31]),
      "+f"(d[32]), "+f"(d[33]), "+f"(d[34]), "+f"(d[35]), "+f"(d[36]), "+f"(d[37]), "+f"(d[38]), "+f"(d[39]),
      "+f"(d[40]), "+f"(d[41]), "+f"(d[42]), "+f"(d[43]), "+f"(d[44]), "+f"(d[45]), "+f"(d[46]), "+f"(d[47]),
      "+f"(d[48]), "+f"(d[49]), "+f"(d[50]), "+f"(d[51]), "+f"(d[52]), "+f"(d[53]), "+f"(d[54]), "+f"(d[55]),
      "+f"(d[56]), "+f"(d[57]), "+f"(d[58]), "+f"(d[59]), "+f"(d[60]), "+f"(d[61]), "+f"(d[62]), "+f"(d[63])
    : "r"(a0), "r"(a1), "r"(a2), "r"(a3), "l"(db));
}
__device__ __forceinline__ void wgp_rs_n128_f32_bf16(float* d, uint32_t a0, uint32_t a1, uint32_t a2, uint32_t a3, uint64_t db, uint32_t sd) {
  asm volatile("{\n.reg .pred p;\nsetp.ne.b32 p, %69, 0;\n"
    "wgmma.mma_async.sync.aligned.m64n128k16.f32.bf16.bf16 "
    "{%0,%1,%2,%3,%4,%5,%6,%7,%8,%9,%10,%11,%12,%13,%14,%15,%16,%17,%18,%19,%20,%21,%22,%23,%24,%25,%26,%27,%28,%29,%30,%31,%32,%33,%34,%35,%36,%37,%38,%39,%40,%41,%42,%43,%44,%45,%46,%47,%48,%49,%50,%51,%52,%53,%54,%55,%56,%57,%58,%59,%60,%61,%62,%63}, "
    "{%64,%65,%66,%67}, %68, p, 1, 1, 1;\n}\n"
    : "+f"(d[0]), "+f"(d[1]), "+f"(d[2]), "+f"(d[3]), "+f"(d[4]), "+f"(d[5]), "+f"(d[6]), "+f"(d[7]),
      "+f"(d[8]), "+f"(d[9]), "+f"(d[10]), "+f"(d[11]), "+f"(d[12]), "+f"(d[13]), "+f"(d[14]), "+f"(d[15]),
      "+f"(d[16]), "+f"(d[17]), "+f"(d[18]), "+f"(d[19]), "+f"(d[20]), "+f"(d[21]), "+f"(d[22]), "+f"(d[23]),
      "+f"(d[24]), "+f"(d[25]), "+f"(d[26]), "+f"(d[27]), "+f"(d[28]), "+f"(d[29]), "+f"(d[30]), "+f"(d[31]),
      "+f"(d[32]), "+f"(d[33]), "+f"(d[34]), "+f"(d[35]), "+f"(d[36]), "+f"(d[37]), "+f"(d[38]), "+f"(d[39]),
      "+f"(d[40]), "+f"(d[41]), "+f"(d[42]), "+f"(d[43]), "+f"(d[44]), "+f"(d[45]), "+f"(d[46]), "+f"(d[47]),
      "+f"(d[48]), "+f"(d[49]), "+f"(d[50]), "+f"(d[51]), "+f"(d[52]), "+f"(d[53]), "+f"(d[54]), "+f"(d[55]),
      "+f"(d[56]), "+f"(d[57]), "+f"(d[58]), "+f"(d[59]), "+f"(d[60]), "+f"(d[61]), "+f"(d[62]), "+f"(d[63])
    : "r"(a0), "r"(a1), "r"(a2), "r"(a3), "l"(db), "r"(sd));
}
__device__ __forceinline__ void wgp_rs_n32_f32_bf16(float* d, uint32_t a0, uint32_t a1, uint32_t a2, uint32_t a3, uint64_t db, uint32_t sd) {
  asm volatile("{\n.reg .pred p;\nsetp.ne.b32 p, %21, 0;\n"
    "wgmma.mma_async.sync.aligned.m64n32k16.f32.bf16.bf16 "
    "{%0,%1,%2,%3,%4,%5,%6,%7,%8,%9,%10,%11,%12,%13,%14,%15}, "
    "{%16,%17,%18,%19}, %20, p, 1, 1, 1;\n}\n"
    : "+f"(d[0]), "+f"(d[1]), "+f"(d[2]), "+f"(d[3]), "+f"(d[4]), "+f"(d[5]), "+f"(d[6]), "+f"(d[7]),
      "+f"(d[8]), "+f"(d[9]), "+f"(d[10]), "+f"(d[11]), "+f"(d[12]), "+f"(d[13]), "+f"(d[14]), "+f"(d[15])
    : "r"(a0), "r"(a1), "r"(a2), "r"(a3), "l"(db), "r"(sd));
}
__device__ __forceinline__ void wg_rs_n32_f32_bf16(float* d, uint32_t a0, uint32_t a1, uint32_t a2, uint32_t a3, uint64_t db) {
  asm volatile("{\n.reg .pred p;\nsetp.ne.b32 p, 1, 0;\n"
    "wgmma.mma_async.sync.aligned.m64n32k16.f32.bf16.bf16 "
    "{%0,%1,%2,%3,%4,%5,%6,%7,%8,%9,%10,%11,%12,%13,%14,%15}, "
    "{%16,%17,%18,%19}, %20, p, 1, 1, 1;\n}\n"
    : "+f"(d[0]), "+f"(d[1]), "+f"(d[2]), "+f"(d[3]), "+f"(d[4]), "+f"(d[5]), "+f"(d[6]), "+f"(d[7]),
      "+f"(d[8]), "+f"(d[9]), "+f"(d[10]), "+f"(d[11]), "+f"(d[12]), "+f"(d[13]), "+f"(d[14]), "+f"(d[15])
    : "r"(a0), "r"(a1), "r"(a2), "r"(a3), "l"(db));
}
__device__ __forceinline__ void wgz_ss_n144_f32_bf16(float* d, uint64_t da, uint64_t db) {
  asm volatile("{\n.reg .pred p;\nsetp.ne.b32 p, 0, 0;\n"
    "wgmma.mma_async.sync.aligned.m64n144k16.f32.bf16.bf16 "
    "{%0,%1,%2,%3,%4,%5,%6,%7,%8,%9,%10,%11,%12,%13,%14,%15,%16,%17,%18,%19,%20,%21,%22,%23,%24,%25,%26,%27,%28,%29,%30,%31,%32,%33,%34,%35,%36,%37,%38,%39,%40,%41,%42,%43,%44,%45,%46,%47,%48,%49,%50,%51,%52,%53,%54,%55,%56,%57,%58,%59,%60,%61,%62,%63,%64,%65,%66,%67,%68,%69,%70,%71}, "
    "%72, %73, p, 1, 1, 0, 1;\n}\n"
    : "=f"(d[0]), "=f"(d[1]), "=f"(d[2]), "=f"(d[3]), "=f"(d[4]), "=f"(d[5]), "=f"(d[6]), "=f"(d[7]),
      "=f"(d[8]), "=f"(d[9]), "=f"(d[10]), "=f"(d[11]), "=f"(d[12]), "=f"(d[13]), "=f"(d[14]), "=f"(d[15]),
      "=f"(d[16]), "=f"(d[17]), "=f"(d[18]), "=f"(d[19]), "=f"(d[20]), "=f"(d[21]), "=f"(d[22]), "=f"(d[23]),
      "=f"(d[24]), "=f"(d[25]), "=f"(d[26]), "=f"(d[27]), "=f"(d[28]), "=f"(d[29]), "=f"(d[30]), "=f"(d[31]),
      "=f"(d[32]), "=f"(d[33]), "=f"(d[34]), "=f"(d[35]), "=f"(d[36]), "=f"(d[37]), "=f"(d[38]), "=f"(d[39]),
      "=f"(d[40]), "=f"(d[41]), "=f"(d[42]), "=f"(d[43]), "=f"(d[44]), "=f"(d[45]), "=f"(d[46]), "=f"(d[47]),
      "=f"(d[48]), "=f"(d[49]), "=f"(d[50]), "=f"(d[51]), "=f"(d[52]), "=f"(d[53]), "=f"(d[54]), "=f"(d[55]),
      "=f"(d[56]), "=f"(d[57]), "=f"(d[58]), "=f"(d[59]), "=f"(d[60]), "=f"(d[61]), "=f"(d[62]), "=f"(d[63]),
      "=f"(d[64]), "=f"(d[65]), "=f"(d[66]), "=f"(d[67]), "=f"(d[68]), "=f"(d[69]), "=f"(d[70]), "=f"(d[71])
    : "l"(da), "l"(db));
}
__device__ __forceinline__ void wg_ss_n144_f32_bf16(float* d, uint64_t da, uint64_t db) {
  asm volatile("{\n.reg .pred p;\nsetp.ne.b32 p, 1, 0;\n"
    "wgmma.mma_async.sync.aligned.m64n144k16.f32.bf16.bf16 "
    "{%0,%1,%2,%3,%4,%5,%6,%7,%8,%9,%10,%11,%12,%13,%14,%15,%16,%17,%18,%19,%20,%21,%22,%23,%24,%25,%26,%27,%28,%29,%30,%31,%32,%33,%34,%35,%36,%37,%38,%39,%40,%41,%42,%43,%44,%45,%46,%47,%48,%49,%50,%51,%52,%53,%54,%55,%56,%57,%58,%59,%60,%61,%62,%63,%64,%65,%66,%67,%68,%69,%70,%71}, "
    "%72, %73, p, 1, 1, 0, 1;\n}\n"
    : "+f"(d[0]), "+f"(d[1]), "+f"(d[2]), "+f"(d[3]), "+f"(d[4]), "+f"(d[5]), "+f"(d[6]), "+f"(d[7]),
      "+f"(d[8]), "+f"(d[9]), "+f"(d[10]), "+f"(d[11]), "+f"(d[12]), "+f"(d[13]), "+f"(d[14]), "+f"(d[15]),
      "+f"(d[16]), "+f"(d[17]), "+f"(d[18]), "+f"(d[19]), "+f"(d[20]), "+f"(d[21]), "+f"(d[22]), "+f"(d[23]),
      "+f"(d[24]), "+f"(d[25]), "+f"(d[26]), "+f"(d[27]), "+f"(d[28]), "+f"(d[29]), "+f"(d[30]), "+f"(d[31]),
      "+f"(d[32]), "+f"(d[33]), "+f"(d[34]), "+f"(d[35]), "+f"(d[36]), "+f"(d[37]), "+f"(d[38]), "+f"(d[39]),
      "+f"(d[40]), "+f"(d[41]), "+f"(d[42]), "+f"(d[43]), "+f"(d[44]), "+f"(d[45]), "+f"(d[46]), "+f"(d[47]),
      "+f"(d[48]), "+f"(d[49]), "+f"(d[50]), "+f"(d[51]), "+f"(d[52]), "+f"(d[53]), "+f"(d[54]), "+f"(d[55]),
      "+f"(d[56]), "+f"(d[57]), "+f"(d[58]), "+f"(d[59]), "+f"(d[60]), "+f"(d[61]), "+f"(d[62]), "+f"(d[63]),
      "+f"(d[64]), "+f"(d[65]), "+f"(d[66]), "+f"(d[67]), "+f"(d[68]), "+f"(d[69]), "+f"(d[70]), "+f"(d[71])
    : "l"(da), "l"(db));
}

typedef __nv_bfloat16 bf16;
constexpr int SEQ = 2048, DM = 576, FF = 4608;
constexpr int NCTA = 128, NHELP = 4, NTHR = 512;

struct LLScratch {
    uint32_t y[72][NCTA][32];
    uint32_t hn[32][8][288];
    uint32_t hs[32][8][288];
    uint4    top[NCTA][64];
};
static_assert(sizeof(LLScratch) % (NHELP * 16) == 0, "zero slices");
struct LLOwn {
    uint32_t o[2304];
    float4   part[64];
};
struct LLFirst {
    uint4 kvx[NCTA][80];
    float2 stat1[SEQ];
    uint32_t info[32];
    uint4 csb[4][64];
};
struct Scratch {
    LLScratch ll;
    LLFirst l1;
    LLOwn own[NCTA];
    uint4 kv[SEQ * 5];
    uint4 o1[NCTA][576];
    uint4 wo[4 * 36 * 288];
    float4 kvraw[SEQ * 10];
    uint32_t tmp[NCTA][NTHR][8];
    uint32_t oflag[NCTA][8];
    uint32_t hflag[NHELP][8];
    uint32_t cnt[96];
};
__device__ __align__(1024) Scratch g_scratch;
constexpr uint32_t CNT1 = NCTA;

#define TS(i)
#define TSG(i)
#define TSL(i)

constexpr int SM_X = 147456;
constexpr int SM_WKV = 61440;
constexpr int SM_OLO = 126976, SM_OHI = 163840;
constexpr int SM_A = 200704;
constexpr int SM_R = 92160;
constexpr int SM_XS = SM_OHI;
constexpr int SM_DN0 = SM_OHI + 20096, SM_DN1 = 73728, SM_DN2 = SM_A;
constexpr int SM_OUT = SM_OLO;
constexpr int SM_HN = 0, SM_RED = 9344;
constexpr int SM_MISC = 221184;
constexpr int SM_BAR = SM_MISC + 10752;
constexpr int SM_TOTAL = 232448;
constexpr int MP_C = 512, MP_N2 = 1088, MP_ST = 1152, MP_VM = 1280, MP_INFO = 1312, MP_P = 2304, MP_STG = 2304, MP_B = 3584, MP_W = 5888;
constexpr int MI_STAT = 0;
constexpr int MI_CS = 512;
constexpr int MI_KP = 1088;
constexpr int MI_TOP = 1152;
constexpr int MI_ACT = 1344;
constexpr int MI_SEL = 2304;
constexpr int MI_ONE = 2560;
constexpr int MI_Z = 6400;
constexpr int SM_SW = SM_TOTAL - 16;
constexpr int SM_ZERO = SM_TOTAL - 8;
enum { B_KV1 = 0, B_KV2, B_AUX = 4, B_ZOK, B_OHT, B_XS, B_DN, B_GU, B_FULL = 10, B_WF = 19, B_KV0 = 27,
       B_G = 28, B_QC = 31, B_PUB = 40, B_KVD = 40, B_OHA = 46, B_END, B_W, B_NUM };
static_assert(B_NUM * 8 <= SM_TOTAL - SM_BAR, "barriers");

constexpr uint32_t sb = 1024;
#define BAR(i) (sb + SM_BAR + 8 * (i))

#define MARK(x)
#define MARKMASK 0
#define WG_FENCE() asm volatile("wgmma.fence.sync.aligned;" ::: "memory")
#define WG_COMMIT() asm volatile("wgmma.commit_group.sync.aligned;" ::: "memory")
#define WG_WAIT(n) asm volatile("wgmma.wait_group.sync.aligned %0;" :: "n"(n) : "memory")
#define BAR_SYNC(id, n) asm volatile("barrier.cta.sync %0, %1;" :: "n"(id), "n"(n) : "memory")
#define BAR_ARRIVE(id, n) asm volatile("barrier.cta.arrive %0, %1;" :: "n"(id), "n"(n) : "memory")
#define PROXY_FENCE_GMEM() asm volatile("fence.proxy.async.global;" ::: "memory")
#define PROXY_FENCE_SMEM() asm volatile("fence.proxy.async.shared::cta;" ::: "memory")

__device__ __forceinline__ constexpr uint64_t mkdesc(uint32_t addr, uint32_t lbo, uint32_t sbo, uint32_t mode) {
    return (uint64_t)((addr & 0x3FFFF) >> 4) | ((uint64_t)(lbo >> 4) << 16) | ((uint64_t)(sbo >> 4) << 32) | ((uint64_t)mode << 62);
}
#define ELECT "{\n.reg .pred e;\nelect.sync _|e, 0xffffffff;\n@e "
__device__ __forceinline__ void mbar_init_e(uint32_t b, int c) { asm volatile(ELECT "mbarrier.init.shared::cta.b64 [%0], %1;\n}" :: "r"(b), "r"(c) : "memory"); }
__device__ __forceinline__ void mbar_expect_e(uint32_t b, uint32_t tx) { asm volatile(ELECT "mbarrier.arrive.expect_tx.shared::cta.b64 _, [%0], %1;\n}" :: "r"(b), "r"(tx) : "memory"); }
__device__ __forceinline__ void mbar_arrive_e(uint32_t b) { asm volatile(ELECT "mbarrier.arrive.shared::cta.b64 _, [%0];\n}" :: "r"(b) : "memory"); }
__device__ __forceinline__ void mbar_arrive_if(uint32_t b, bool c) {
    asm volatile("{.reg .pred p; setp.ne.u32 p, %1, 0; @p mbarrier.arrive.shared::cta.b64 _, [%0];}" :: "r"(b), "r"((uint32_t)c) : "memory");
}
__device__ __forceinline__ bool mbar_test(uint32_t b) {
    uint32_t ok;
    asm volatile("{.reg .pred p; mbarrier.test_wait.parity.shared::cta.b64 p, [%1], 0; selp.u32 %0, 1, 0, p;}" : "=r"(ok) : "r"(b) : "memory");
    return __all_sync(~0u, ok);
}
#define GIVEUP(n) "@!p st.shared.u32 [c], c;\n"
#define LIMIT "0x400000"
#define WAITFN template <int LN> __device__ __forceinline__
#define SPIN_HEAD "{\n.reg .pred p, q;\n.reg .u32 c, v;\nmov.u32 c, 0;\nW: .pragma \"nounroll\";\n"
#define SPIN_TAIL(n) "add.u32 c, c, 1;\nsetp.lt.and.u32 q, c, " LIMIT ", !p;\n@q bra.uni W;\n" GIVEUP(n) "}"
WAITFN void mbar_wait_(uint32_t b) {
    asm volatile(SPIN_HEAD "mbarrier.try_wait.parity.shared::cta.b64 p, [%0], 0;\n" SPIN_TAIL(1) :: "r"(b), "n"(LN) : "memory");
}
#define mbar_wait(b) mbar_wait_<__LINE__>(b)
__device__ __forceinline__ void bulk_ld_e(uint32_t dst, const void* src, uint32_t bytes, uint32_t bar) {
    asm volatile(ELECT "cp.async.bulk.shared::cluster.global.mbarrier::complete_tx::bytes [%0], [%1], %2, [%3];\n}"
                 :: "r"(dst), "l"(src), "r"(bytes), "r"(bar) : "memory");
}
__device__ __forceinline__ void bulk_st_e(void* dst, uint32_t src, uint32_t bytes) {
    asm volatile(ELECT "cp.async.bulk.global.shared::cta.bulk_group [%0], [%1], %2;\n}" :: "l"(dst), "r"(src), "r"(bytes) : "memory");
}
__device__ __forceinline__ void tma2d_e(uint32_t dst, const CUtensorMap* tm, int c0, int c1, uint32_t bar) {
    asm volatile(ELECT "cp.async.bulk.tensor.2d.shared::cluster.global.mbarrier::complete_tx::bytes [%0], [%1, {%3, %4}], [%2];\n}"
                 :: "r"(dst), "l"(tm), "r"(bar), "r"(c0), "r"(c1) : "memory");
}
__device__ __forceinline__ void tma3d_e(uint32_t dst, const CUtensorMap* tm, int c0, int c1, int c2, uint32_t bar) {
    asm volatile(ELECT "cp.async.bulk.tensor.3d.shared::cluster.global.mbarrier::complete_tx::bytes [%0], [%1, {%3, %4, %5}], [%2];\n}"
                 :: "r"(dst), "l"(tm), "r"(bar), "r"(c0), "r"(c1), "r"(c2) : "memory");
}
__device__ __forceinline__ void tma2d_st_e(const CUtensorMap* tm, int c0, int c1, uint32_t src) {
    asm volatile(ELECT "cp.async.bulk.tensor.2d.global.shared::cta.bulk_group [%0, {%2, %3}], [%1];\n}" :: "l"(tm), "r"(src), "r"(c0), "r"(c1) : "memory");
}
__device__ __forceinline__ void l2_prefetch_e(const void* src, uint32_t bytes) {
    asm volatile(ELECT "cp.async.bulk.prefetch.L2.global [%0], %1;\n}" :: "l"(src), "r"(bytes) : "memory");
}
__device__ __forceinline__ void tm_prefetch_e(const CUtensorMap* tm) { asm volatile(ELECT "prefetch.tensormap [%0];\n}" :: "l"(tm) : "memory"); }
__device__ __forceinline__ void red_release_e(uint32_t* p) { asm volatile(ELECT "red.release.gpu.global.add.u32 [%0], 1;\n}" :: "l"(p) : "memory"); }
__device__ __forceinline__ void red_max(uint32_t* p, uint32_t v) { asm volatile("red.relaxed.gpu.global.max.u32 [%0], %1;" :: "l"(p), "r"(v) : "memory"); }
__device__ __forceinline__ void red_relaxed_e(uint32_t* p) { asm volatile(ELECT "red.relaxed.gpu.global.add.u32 [%0], 1;\n}" :: "l"(p) : "memory"); }
WAITFN void poll_counter_(const uint32_t* p, uint32_t target) {
    asm volatile(SPIN_HEAD "ld.acquire.gpu.global.u32 v, [%0];\nsetp.ge.u32 p, v, %1;\n" SPIN_TAIL(2) :: "l"(p), "r"(target), "n"(LN) : "memory");
}
#define poll_counter(p, t) poll_counter_<__LINE__>(p, t)
__device__ __forceinline__ uint4 ld_rlx16(const void* p) {
    uint4 v;
    asm volatile("ld.relaxed.gpu.global.v4.u32 {%0,%1,%2,%3}, [%4];" : "=r"(v.x), "=r"(v.y), "=r"(v.z), "=r"(v.w) : "l"(p) : "memory");
    return v;
}
__device__ __forceinline__ uint32_t ld_rlx4(const void* p) {
    uint32_t v;
    asm volatile("ld.relaxed.gpu.global.u32 %0, [%1];" : "=r"(v) : "l"(p) : "memory");
    return v;
}
template <int LN, int N, int S> __device__ __forceinline__ void ll_load_(uint4* v, const uint4* p, const uint4* plast) {
    uint32_t c = 0, again;
#pragma unroll 1
    do {
        uint32_t m = ~0u;
#pragma unroll
        for (int i = 0; i < N; i++) v[i] = ld_rlx16(i < N - 1 ? p + i * S : plast);
#pragma unroll
        for (int i = 0; i < N; i++) m = min(min(m, v[i].x), min(min(v[i].y, v[i].z), v[i].w));
        c++;
        asm volatile("{\n.reg .pred p, q;\n.reg .u32 c;\nmov.u32 c, %1;\nsetp.lt.u32 p, c, " LIMIT ";\nsetp.eq.and.u32 q, %2, 0, p;\nselp.u32 %0, 1, 0, q;\n" GIVEUP(3) "}"
                     : "=r"(again) : "r"(c), "r"(m), "n"(LN) : "memory");
    } while (__any_sync(~0u, again));
}
template <int N, int S> __device__ __forceinline__ void ll_issue(uint4* v, const uint4* p, const uint4* plast) {
#pragma unroll
    for (int i = 0; i < N; i++) v[i] = ld_rlx16(i < N - 1 ? p + i * S : plast);
}
template <int N> __device__ __forceinline__ bool ll_missing(const uint4* v) {
    uint32_t m = ~0u;
#pragma unroll
    for (int i = 0; i < N; i++) m = min(min(m, v[i].x), min(min(v[i].y, v[i].z), v[i].w));
    return __any_sync(~0u, m == 0);
}
#define ll_load(N, S, v, p) ll_load_<__LINE__, N, S>(v, p, (p) + ((N) - 1) * (S))
#define ll_load2(N, S, v, p, plast) ll_load_<__LINE__, N, S>(v, p, plast)
WAITFN uint32_t ll_load4_(const void* p) {
    uint32_t r;
    asm volatile(SPIN_HEAD "ld.relaxed.gpu.global.u32 %0, [%1];\nsetp.ne.u32 q, %0, 0;\nvote.sync.all.pred p, q, 0xffffffff;\n" SPIN_TAIL(2)
                 : "=&r"(r) : "l"(p), "n"(LN) : "memory");
    return r;
}
#define ll_load4(p) ll_load4_<__LINE__>(p)
__device__ __forceinline__ void st_rlx4(void* p, uint32_t a) { asm volatile("st.relaxed.gpu.global.u32 [%0], %1;" :: "l"(p), "r"(a) : "memory"); }
__device__ __forceinline__ void st_rlx4_if(void* p, uint32_t a, bool c) {
    asm volatile("{.reg .pred p; setp.ne.u32 p, %2, 0; @p st.relaxed.gpu.global.u32 [%0], %1;}" :: "l"(p), "r"(a), "r"((uint32_t)c) : "memory");
}
__device__ __forceinline__ void st_rlx8(void* p, uint32_t a, uint32_t b) { asm volatile("st.relaxed.gpu.global.v2.u32 [%0], {%1,%2};" :: "l"(p), "r"(a), "r"(b) : "memory"); }
__device__ __forceinline__ void st_rlx16(void* p, uint32_t a, uint32_t b, uint32_t c, uint32_t d) {
    asm volatile("st.relaxed.gpu.global.v4.u32 [%0], {%1,%2,%3,%4};" :: "l"(p), "r"(a), "r"(b), "r"(c), "r"(d) : "memory");
}
__device__ __forceinline__ uint32_t nz(uint32_t w) { return max(w, 1u); }
__device__ __forceinline__ uint32_t nzf(float f) { return max(__float_as_uint(f), 1u); }
__device__ __forceinline__ void mma_bf16(float* d, uint32_t a0, uint32_t a1, uint32_t a2, uint32_t a3, uint32_t b0, uint32_t b1) {
    asm volatile("mma.sync.aligned.m16n8k16.row.col.f32.bf16.bf16.f32 {%0,%1,%2,%3}, {%4,%5,%6,%7}, {%8,%9}, {%0,%1,%2,%3};"
                 : "+f"(d[0]), "+f"(d[1]), "+f"(d[2]), "+f"(d[3]) : "r"(a0), "r"(a1), "r"(a2), "r"(a3), "r"(b0), "r"(b1));
}
__device__ __forceinline__ void mma_bf16_k8(float* d, uint32_t a0, uint32_t a1, uint32_t b0) {
    asm volatile("mma.sync.aligned.m16n8k8.row.col.f32.bf16.bf16.f32 {%0,%1,%2,%3}, {%4,%5}, {%6}, {%0,%1,%2,%3};"
                 : "+f"(d[0]), "+f"(d[1]), "+f"(d[2]), "+f"(d[3]) : "r"(a0), "r"(a1), "r"(b0));
}
__device__ __forceinline__ void delay(uint32_t cyc) {
    asm volatile("{\n.reg .pred p;\n.reg .u32 c, c0;\nmov.u32 c0, %%clock;\nW: .pragma \"nounroll\";\nmov.u32 c, %%clock;\nsub.u32 c, c, c0;\n"
                 "setp.lt.u32 p, c, %0;\n@p bra.uni W;\n}" :: "r"(cyc) : "memory");
}
__device__ __forceinline__ int fresh_tid() { int v; asm volatile("mov.u32 %0, %%tid.x;" : "=r"(v)); return v; }
__device__ __forceinline__ float sq_h2(uint32_t w) { float2 f = __half22float2(*(__half2*)&w); return f.x * f.x + f.y * f.y; }
__device__ __forceinline__ void ldsm4(uint32_t* r, uint32_t a) {
    asm volatile("ldmatrix.sync.aligned.m8n8.x4.shared.b16 {%0,%1,%2,%3}, [%4];" : "=r"(r[0]), "=r"(r[1]), "=r"(r[2]), "=r"(r[3]) : "r"(a) : "memory");
}
__device__ __forceinline__ void ldsm4t(uint32_t* r, uint32_t a) {
    asm volatile("ldmatrix.sync.aligned.m8n8.x4.trans.shared.b16 {%0,%1,%2,%3}, [%4];" : "=r"(r[0]), "=r"(r[1]), "=r"(r[2]), "=r"(r[3]) : "r"(a) : "memory");
}
__device__ __forceinline__ void stsm4(uint32_t a, uint32_t r0, uint32_t r1, uint32_t r2, uint32_t r3) {
    asm volatile("stmatrix.sync.aligned.m8n8.x4.shared.b16 [%0], {%1,%2,%3,%4};" :: "r"(a), "r"(r0), "r"(r1), "r"(r2), "r"(r3) : "memory");
}
__device__ __forceinline__ float frcp(float x) { float r; asm("rcp.approx.ftz.f32 %0, %1;" : "=f"(r) : "f"(x)); return r; }
__device__ __forceinline__ float fsqrt(float x) { float r; asm("sqrt.approx.ftz.f32 %0, %1;" : "=f"(r) : "f"(x)); return r; }
__device__ __forceinline__ float bfr(float x) { return __bfloat162float(__float2bfloat16_rn(x)); }
__device__ __forceinline__ uint32_t pk_bf(float lo, float hi) { uint32_t r; asm("cvt.rn.bf16x2.f32 %0, %1, %2;" : "=r"(r) : "f"(hi), "f"(lo)); return r; }
__device__ __forceinline__ uint32_t pk_h(float lo, float hi) { uint32_t r; asm("cvt.rn.f16x2.f32 %0, %1, %2;" : "=r"(r) : "f"(hi), "f"(lo)); return r; }
__device__ __forceinline__ float bf_lo(uint32_t w) { return __uint_as_float(w << 16); }
__device__ __forceinline__ float bf_hi(uint32_t w) { return __uint_as_float(w & 0xFFFF0000u); }
__device__ __forceinline__ uint32_t add_bf2(uint32_t a, uint32_t b) { uint32_t r; asm("add.rn.bf16x2 %0, %1, %2;" : "=r"(r) : "r"(a), "r"(b)); return r; }
__device__ __forceinline__ uint32_t sub_bf2(uint32_t a, uint32_t b) { uint32_t r; asm("sub.rn.bf16x2 %0, %1, %2;" : "=r"(r) : "r"(a), "r"(b)); return r; }
__device__ __forceinline__ float2 ln_stats(float sx, float sxx) {
    float mean = sx * (1.0f / DM);
    float var = fmaxf(sxx * (1.0f / DM) - mean * mean, 0.0f);
    float s = bfr(fsqrt(bfr(bfr(var) + 1e-5f)));
    return make_float2(bfr(mean), frcp(s));
}
__device__ __forceinline__ uint32_t ln_apply(uint32_t w, uint32_t m2, float inv) {
    uint32_t d = sub_bf2(w, m2);
    return pk_bf(bf_lo(d) * inv, bf_hi(d) * inv);
}

__device__ __forceinline__ uint32_t or3(uint32_t a, uint32_t b, uint32_t c) { uint32_t r; asm("lop3.b32 %0, %1, %2, %3, 0xFE;" : "=r"(r) : "r"(a), "r"(b), "r"(c)); return r; }
__device__ __forceinline__ uint32_t ex2_mufu(uint32_t v) { uint32_t r; asm("ex2.approx.f16x2 %0, %1;" : "=r"(r) : "r"(v)); return r; }
__device__ __forceinline__ uint32_t hfma2(uint32_t a, uint32_t b, uint32_t c) { uint32_t r; asm("fma.rn.f16x2 %0, %1, %2, %3;" : "=r"(r) : "r"(a), "r"(b), "r"(c)); return r; }
__device__ __forceinline__ uint32_t ex2_poly(uint32_t w, uint32_t cz, uint32_t ca) {
    uint32_t z;
    asm("lop3.b32 %0, %1, 0x003F003F, %2, 0xEA;" : "=r"(z) : "r"(w), "r"(cz));
    uint32_t q = hfma2(z, ca, 0xE794E794u);
    uint32_t h = hfma2(q, q, 0x7BA97BA9u);
    return __funnelshift_l(w, w, 4) + h;
}
constexpr uint32_t POLY_CZ = 0x3C803C80u, POLY_CA = 0x668D668Du;

struct Params {
    Scratch* g;
    const bf16 *x, *wk, *wv, *wq, *wo, *wr, *wg, *wu, *wd;
    bf16* out;
};

extern __shared__ __align__(1024) uint8_t smem[];

__device__ __forceinline__ void attn_safe(const Scratch* G, const bf16* x, const bf16* wq, int row0, int head, uint32_t* res) {
    const int lane = threadIdx.x & 31, half = lane & 1, row = row0 + (lane >> 1);
    const float2 st = ((const float2*)(smem + SM_MISC + MI_STAT))[row & 63];
    float q[18];
#pragma unroll
    for (int d = 0; d < 18; d++) q[d] = 0.f;
#pragma unroll 1
    for (int i = half * 288; i < half * 288 + 288; i++) {
        float xn = bfr(bfr(__bfloat162float(x[row * DM + i]) - st.x) * st.y);
#pragma unroll
        for (int d = 0; d < 18; d++) q[d] += xn * __bfloat162float(wq[i * DM + head * 18 + d]);
    }
#pragma unroll
    for (int d = 0; d < 18; d++) q[d] = bfr(q[d] + __shfl_xor_sync(~0u, q[d], 1)) * 0.23570226039551584f;
    float o[18], l = 0.f, m = -INFINITY;
#pragma unroll
    for (int d = 0; d < 18; d++) o[d] = 0.f;
#pragma unroll 1
    for (int pass = 0; pass < 2; pass++) {
#pragma unroll 1
        for (int k = half * 1024; k < half * 1024 + 1024; k++) {
            const float4* p = G->kvraw + k * 10;
            float4 e = __ldcg(p + 8);
            float s = q[16] * e.x + q[17] * e.y;
#pragma unroll
            for (int j = 0; j < 4; j++) { float4 a = __ldcg(p + j); s += q[4*j] * a.x + q[4*j+1] * a.y + q[4*j+2] * a.z + q[4*j+3] * a.w; }
            if (pass == 0) { m = fmaxf(m, s); }
            else {
                float pr = __expf(s - m);
                l += pr; o[16] += pr * e.z; o[17] += pr * e.w;
#pragma unroll
                for (int j = 0; j < 4; j++) { float4 a = __ldcg(p + 4 + j); o[4*j] += pr * a.x; o[4*j+1] += pr * a.y; o[4*j+2] += pr * a.z; o[4*j+3] += pr * a.w; }
            }
        }
        if (pass == 0) m = fmaxf(m, __shfl_xor_sync(~0u, m, 1));
    }
    l += __shfl_xor_sync(~0u, l, 1);
    const float inv = frcp(l);
    const int g = lane >> 2, t = lane & 3;
#pragma unroll
    for (int p = 0; p < 9; p++) {
        float a = o[2*p] + __shfl_xor_sync(~0u, o[2*p], 1), b = o[2*p+1] + __shfl_xor_sync(~0u, o[2*p+1], 1);
        uint32_t w = pk_bf(a * inv, b * inv);
        uint32_t v0 = __shfl_sync(~0u, w, 2 * g), v1 = __shfl_sync(~0u, w, 2 * g + 16);
        if (p == 2 * t) { res[2] = v0; res[3] = v1; }
        if (p == 2 * t + 1) { res[4] = v0; res[5] = v1; }
        if (p == 8) { res[0] = v0; res[1] = v1; }
    }
}

#define NSPLIT 1
#define GATE 1
#define XPF 0
#define DPF 1
#define XAT 3
#define WPF 0
#define DNLATE 0
#define DLY0 400
#define DLYO 0
#define DLY1 200
#define DLY2 400
#define DLY3 500
#define OUT_LATE 1

__device__ __forceinline__ void agent_job(Scratch* G, const CUtensorMap* tm_g, const CUtensorMap* tm_u, int warp, int& st, bool fin) {
    const int cta = blockIdx.x - NHELP, hg = cta & 3;
    if (warp == 4) {
#pragma unroll 1
        while (st < 2) {
            if (st == 0) {
                if (fin) mbar_wait(BAR(B_OHA)); else if (!mbar_test(BAR(B_OHA))) break;
                bulk_st_e(G->o1[cta], sb + SM_OHI, 9216);
                bulk_st_e(&G->own[cta], sb + SM_MISC + MI_Z, 4096); bulk_st_e(G->own[cta].o + 1024, sb + SM_MISC + MI_Z, 4096);
                bulk_st_e(G->own[cta].o + 2048, sb + SM_MISC + MI_Z, 2048);
                asm volatile("cp.async.bulk.commit_group;" ::: "memory");
            } else {
                asm volatile("cp.async.bulk.wait_group 0;" ::: "memory");
                PROXY_FENCE_GMEM();
                red_relaxed_e(G->oflag[cta]);
            }
            st++;
            if (!fin) break;
        }
    } else if (warp == 8) {
        if (st == 0) {
            const int l = fresh_tid() & 7;
            const uint32_t* fp = l < 4 ? G->oflag[(cta & ~3) + l] : G->hflag[l - 4];
            const uint32_t f = fin ? ll_load4(fp) : ld_rlx4(fp);
            if (__all_sync(~0u, f != 0)) {
                asm volatile("fence.acquire.gpu;" ::: "memory");
                PROXY_FENCE_GMEM();
                mbar_arrive_e(BAR(B_ZOK));
                TS(7);
                mbar_expect_e(BAR(B_OHT), 3 * 9216);
#pragma unroll 1
                for (int u = 1; u < 4; u++) bulk_ld_e(sb + SM_OHI + u * 9216, G->o1[(cta & ~3) + ((hg + u) & 3)], 9216, BAR(B_OHT));
                st = 1;
            }
        }
    } else {
#pragma unroll 1
        while (st < 6) {
            const uint32_t wb = st < 5 ? BAR(B_KVD + 1 + st) : BAR(B_ZOK);
            if (fin) mbar_wait(wb); else if (!mbar_test(wb)) break;
            if (st < 4) {
                const int fc0 = (cta * 36) & ~7;
                if (st == 0) mbar_expect_e(BAR(B_GU), 4 * 23040);
                tma2d_e(sb + st * 23040, tm_g, fc0, st * 144, BAR(B_GU));
                tma2d_e(sb + st * 23040 + 11520, tm_u, fc0, st * 144, BAR(B_GU));
            } else if (st == 5) {
                mbar_expect_e(BAR(B_WF), 5 * 9216);
                bulk_ld_e(sb + SM_A, G->wo + hg * 10368, 2 * 9216, BAR(B_WF));
                bulk_ld_e(sb + SM_R, G->wo + hg * 10368 + 2 * 576, 3 * 9216, BAR(B_WF));
            }
            st++;
        }
    }
}

__device__ __forceinline__ void load_q(uint32_t* q, int head) {
    const int tid = fresh_tid(), t = tid & 3;
    const uint8_t* qs = smem + SM_A + (((tid >> 5) & 3) * 16 + ((tid & 31) >> 2)) * 304 + head * 36;
    q[0] = *(const uint32_t*)(qs + 4 * t); q[1] = *(const uint32_t*)(qs + 8 * 304 + 4 * t);
    q[2] = *(const uint32_t*)(qs + 16 + 4 * t); q[3] = *(const uint32_t*)(qs + 8 * 304 + 16 + 4 * t);
    q[4] = *(const uint32_t*)(qs + 32); q[5] = *(const uint32_t*)(qs + 8 * 304 + 32);
    if (t != 0) { q[4] = t == 1 ? 0x1800u : 0u; q[5] = q[4]; }
}
__device__ __forceinline__ bool check_o(const float* o, uint32_t accor, float& l0, float& l1) {
    const int src = ((fresh_tid() & 28) | 1);
    l0 = __shfl_sync(~0u, o[1], src); l1 = __shfl_sync(~0u, o[3], src);
    return __any_sync(~0u, (accor & 0xF800F800u) || !(fminf(l0, l1) >= 64.0f && l0 + l1 <= 1e30f));
}
__device__ __forceinline__ void pack_o(const float* o, float l0, float l1, uint32_t* ow) {
    const float i0 = frcp(l0), i1 = frcp(l1);
#pragma unroll
    for (int i = 0; i < 6; i++) ow[i] = pk_bf(o[2*i] * ((i & 1) ? i1 : i0), o[2*i+1] * ((i & 1) ? i1 : i0));
}
__device__ __forceinline__ void stage_o(int base, const uint32_t* ow) {
    const int tid = fresh_tid(), t = tid & 3, wg = tid >> 7;
    uint8_t* so = smem + base + (((tid >> 5) & 3) * 16 + ((tid & 31) >> 2)) * 16;
    uint8_t* s1 = so + (2 * wg + (t >> 1)) * 1024 + (t & 1) * 8;
    *(uint2*)s1 = make_uint2(ow[2], ow[4]); *(uint2*)(s1 + 128) = make_uint2(ow[3], ow[5]);
    if (t == 3) { *(uint32_t*)(so + 8192 + wg * 4) = ow[0]; *(uint32_t*)(so + 8320 + wg * 4) = ow[1]; }
}

__device__ __noinline__ void rare_finish(const Params& P, const CUtensorMap* tm_g, const CUtensorMap* tm_u, int warp, int st, uint32_t redo) {
    Scratch* const G = P.g;
    const int cta = blockIdx.x - NHELP;
    warp = __shfl_sync(~0u, warp, 0); st = __shfl_sync(~0u, st, 0); redo = __shfl_sync(~0u, redo, 0);
#pragma unroll 1
    for (int r = 0; r < 2; r++) {
        if ((redo >> r) & 1) {
            uint32_t res[6];
            attn_safe(G, P.x, P.wq, (cta >> 2) * 64 + (warp & 3) * 16, (cta & 3) * 8 + 4 * r + (warp >> 2), res);
            if (r == 0) { stage_o(SM_OHI, res); PROXY_FENCE_SMEM(); mbar_arrive_e(BAR(B_OHA)); }
            else {
#pragma unroll
                for (int i = 0; i < 6; i++) G->tmp[cta][threadIdx.x][i] = res[i];
            }
        }
    }
    if (warp == 4 || warp == 8 || warp == 12) agent_job(G, tm_g, tm_u, warp, st, true);
}

__device__ __forceinline__ void load_chunk(const CUtensorMap* tm_xw, const CUtensorMap* tm_wqt, int xi, int c, int sl) {
    const int hg = blockIdx.x & 3, w0 = (9 * hg >> 1) * 32;
    const uint32_t slot = sb + sl * 20480, bar = BAR(B_FULL + c);
    tma3d_e(slot, tm_xw, w0 + (hg & 2) * 16, c * 64, xi ^ 1, bar);
    tma3d_e(slot + 8192, tm_xw, w0 + (hg & 2) * 16 + 64, c * 64, xi ^ 1, bar);
    tma2d_e(slot + 16384, tm_wqt, w0 + ((hg & 2) ? 0 : 128), c * 64, bar);
}

__device__ __forceinline__ void helper(const Params& P, const CUtensorMap* tm_xw, const CUtensorMap* tm_wqt, int warp) {
    Scratch* const G = P.g;
    const int hb = blockIdx.x, tid = threadIdx.x, lane = tid & 31, g = lane >> 2, t = lane & 3;
    constexpr int HZ = 184320, HB = HZ + 32768;
    if (warp < 4) {
        float acc[80];
        uint32_t on[4];
#pragma unroll
        for (int i = 0; i < 4; i++) on[i] = 0x3F803F80u + *(volatile uint32_t*)(smem + SM_ZERO);
#pragma unroll 1
        for (int c = 0; c < 9; c++) {
            const uint64_t db = mkdesc(sb, 8192, 1024, 1) + c * 1280, dt = mkdesc(sb + 16384, 512, 512, 2) + c * 1280;
            mbar_wait(BAR(B_FULL + c));
            WG_FENCE();
            wgp_rs_n128_f32_bf16(acc, on[0], on[1], on[2], on[3], db, c); wgp_rs_n32_f32_bf16(acc + 64, on[0], on[1], on[2], on[3], dt, c);
#pragma unroll
            for (int s = 1; s < 4; s++) { wg_rs_n128_f32_bf16(acc, on[0], on[1], on[2], on[3], db + 128 * s); wg_rs_n32_f32_bf16(acc + 64, on[0], on[1], on[2], on[3], dt + 64 * s); }
            WG_COMMIT();
        }
        WG_WAIT(0);
#pragma unroll
        for (int i = 0; i < 80; i++) asm volatile("" : "+f"(acc[i]) :: "memory");
        if (tid < 4) {
#pragma unroll
            for (int b = 0; b < 20; b++) ((float2*)(smem + HB + 1024))[4 * b + t] = make_float2(acc[4*b], acc[4*b+1]);
        }
        BAR_SYNC(4, 128);
        const int b = 8 * warp + g, wb = (hb & 2) ? (b < 16 ? b + 4 : b - 16) : b;
        const float2 e = ((const float2*)(smem + HB + 1024))[tid];
        const float h0 = bfr(e.x), h1 = bfr(e.y), m0 = bfr(e.x - h0), m1 = bfr(e.y - h1);
        uint32_t* bp = (uint32_t*)(smem + HB) + wb * 12 + t;
        if (b < 20) { bp[0] = pk_bf(h0, h1); bp[4] = pk_bf(m0, m1); bp[8] = pk_bf(e.x - h0 - m0, e.y - h1 - m1); }
    } else if (warp == 4) {
#pragma unroll 1
        for (int c = 0; c < 9; c++) { mbar_expect_e(BAR(B_FULL + c), 20480); load_chunk(tm_xw, tm_wqt, P.x > P.wq, c, c); }
    } else if (warp == 5) {
        const uint2* wp = (const uint2*)P.wr + lane;
        float s = 0.f;
#pragma unroll
        for (int i = 0; i < 5; i++) if (i < 4 || lane < 16) { const uint2 w = __ldg(wp + 32 * i); s += (bf_lo(w.x) + bf_hi(w.x)) + (bf_lo(w.y) + bf_hi(w.y)); }
#pragma unroll
        for (int d = 1; d < 32; d <<= 1) s += __shfl_xor_sync(~0u, s, d);
        ((float*)(smem + HB + 960))[lane & 15] = s;
    } else if (warp >= 8) {
#pragma unroll
        for (int i = 0; i < 8; i++) ((uint4*)(smem + HZ))[i * 256 + tid - 256] = make_uint4(0, 0, 0, 0);
        PROXY_FENCE_SMEM();
    }
    BAR_SYNC(1, 512);
    if (warp < 2) { const uint4 v = ((const uint4*)(smem + HB))[tid]; st_rlx16(&G->l1.csb[hb][tid], nz(v.x), nz(v.y), nz(v.z), nz(v.w)); }
    if (warp == 0) {
        constexpr int ZB = sizeof(LLScratch) / NHELP;
#pragma unroll 1
        for (int off = 0; off < ZB; off += 32768) bulk_st_e((uint8_t*)&G->ll + hb * ZB + off, sb + HZ, min(32768, ZB - off));
        asm volatile("cp.async.bulk.commit_group;\ncp.async.bulk.wait_group 0;" ::: "memory");
        PROXY_FENCE_GMEM();
    } else {
#pragma unroll 1
        for (int i0 = 0; i0 < 2; i0++) {
            uint4 v[11];
            uint32_t dst[11];
#pragma unroll
            for (int u = 0; u < 11; u++) {
                const int i = min((i0 * 11 + u) * 15 + warp - 1, 323);
                const int un = hb * 18 + i / 18, e = i & 1, cc = ((i % 18) >> 1) * 8 + g;
                const int r = un / 36, hs = (un % 36) / 9, w = un % 9, j = 4 * e + t, h2 = cc / 18;
                const int d = w < 8 ? 18 * (w >> 1) + 8 * (w & 1) + j : 18 * (j >> 1) + 16 + (j & 1);
                dst[u] = h2 * 10368 + (36 * r + 9 * ((hs - h2) & 3) + w) * 144 + (cc % 18) * 8 + j;
                v[u] = ld_rlx16((const uint4*)P.wo + (144 * hs + 72 * r + d) * 72 + cc);
            }
#pragma unroll
            for (int u = 0; u < 11; u++) G->wo[dst[u]] = v[u];
        }
    }
    BAR_SYNC(3, 512);
    if (warp != 0) return;
    red_release_e(G->hflag[hb]);
    if (hb == 0) {
        poll_counter(&G->cnt[64], NCTA);
        PROXY_FENCE_GMEM();
#pragma unroll 1
        for (int off = 0; off < (int)sizeof(LLFirst); off += 32768) bulk_st_e((uint8_t*)&G->l1 + off, sb + HZ, min(32768, (int)sizeof(LLFirst) - off));
        asm volatile("cp.async.bulk.commit_group;\ncp.async.bulk.wait_group 0;" ::: "memory");
        G->cnt[0] = 0; G->cnt[64] = 0;
    }
}

extern "C" __global__ void __launch_bounds__(NTHR, 1)
fused_block(const __grid_constant__ Params P, const __grid_constant__ CUtensorMap tm_xw,
            const __grid_constant__ CUtensorMap tm_wqt, const __grid_constant__ CUtensorMap tm_g,
            const __grid_constant__ CUtensorMap tm_u, const __grid_constant__ CUtensorMap tm_xs,
            const __grid_constant__ CUtensorMap tm_d, const __grid_constant__ CUtensorMap tm_o) {
    int tid = threadIdx.x, lane = tid & 31;
    const int warp = __shfl_sync(~0u, tid >> 5, 0);
    const int cta = blockIdx.x - NHELP, qb = cta >> 2, hg = cta & 3;
    int g = lane >> 2, t = lane & 3;
    uint8_t* const misc = smem + SM_MISC;
    const int wg = warp >> 2, wq4 = warp & 3;
    constexpr uint32_t ONE2 = 0x3F803F80u;
    Scratch* const G = P.g;
    if (warp == 0) { TSG(32); TS(0); }
    if (warp == 15) {
        uint32_t c0, c1;
        asm volatile("{\n.reg .u64 a, b;\nmov.u64 a, fused_block_param_0;\ncvt.u64.u32 b, %2;\nadd.u64 a, a, b;\n"
                     "ld.param.u32 %0, [a+-120];\nld.param.u32 %1, [a+64];\n}" : "=r"(c0), "=r"(c1) : "r"(tid >> 10));
        if (cta >= 0) {
            mbar_init_e(BAR(B_W), 1);
            mbar_expect_e(BAR(B_W), 2 * 20736);
            bulk_ld_e(sb + SM_WKV, P.wk, 18432, BAR(B_W));
            bulk_ld_e(sb + SM_WKV + 18432, P.wv, 18432, BAR(B_W));
            bulk_ld_e(sb + SM_MISC + MP_W, P.wk + 9216, 2304, BAR(B_W));
            bulk_ld_e(sb + SM_MISC + MP_W + 2304, P.wv + 9216, 2304, BAR(B_W));
            if (WPF) l2_prefetch_e(P.wq + cta * 2592, 5184);
            if (XPF) l2_prefetch_e(P.x + cta * 16 * DM, 16 * DM * 2);
        }
        asm volatile("st.shared.v4.u32 [%0], {%1,%2,%3,%3};" :: "r"(sb + SM_SW), "r"(c0), "r"(c1), "r"(0) : "memory");
    } else if (warp < 12) {
        const int cnt = warp < 7 ? 1 : (warp < 10 ? 4 : 16);
        asm volatile(ELECT "mbarrier.init.shared::cta.b64 [%0], %1;\n@e mbarrier.init.shared::cta.b64 [%0+8], %1;\n"
                     "@e mbarrier.init.shared::cta.b64 [%0+16], %1;\n@e mbarrier.init.shared::cta.b64 [%0+24], %1;\n"
                     "fence.mbarrier_init.release.cluster;\n}" :: "r"(BAR(warp * 4)), "r"(cnt) : "memory");
    }
    BAR_SYNC(0, 512);
    if (cta < 0) { helper(P, &tm_xw, &tm_wqt, warp); return; }
    if (warp == 0) TS(35);

    if (wg == 0) {
        if (warp == 0) {
            const int xi = P.x > P.wq;
            if (DPF) asm volatile("prefetch.L2 [%0];" :: "l"(&tm_wqt) : "memory");
            if (lane < 9) asm volatile("mbarrier.arrive.expect_tx.shared::cta.b64 _, [%0], %1;" :: "r"(BAR(B_FULL + lane)), "r"(8192 + 20480) : "memory");
            __syncwarp();
#pragma unroll 1
            for (int c = 0; c < 7; c++) {
                if (c == XAT) {
#pragma unroll 1
                    for (int u = 0; u < 9; u++) tma3d_e(sb + SM_X + u * 8192, &tm_xw, u * 64, qb * 64, xi, BAR(B_FULL + u));
                }
                if (c == 5) BAR_SYNC(8, 320);
                load_chunk(&tm_xw, &tm_wqt, xi, c, c < 2 ? c + 5 : c - 2);
            }
        }
        if (warp == 0) TS(36);
        BAR_SYNC(GATE, GATE == 1 ? 416 : 384);
        float acc[80];
#pragma unroll 1
        for (int c = 0; c < 9; c++) {
            const uint32_t slot = (c < 2 ? c + 5 : c - 2) * 1280;
            const uint64_t da = mkdesc(sb + SM_X, 16, 1024, 1) + c * 512;
            const uint64_t db = mkdesc(sb, 8192, 1024, 1) + slot, dt = mkdesc(sb + 16384, 512, 512, 2) + slot;
            mbar_wait(BAR(B_FULL + c));
            if (c == 0) TS(8);
            WG_FENCE();
            wgp_ss_n128_f32_bf16(acc, da, db, c); wgp_ss_n32_f32_bf16(acc + 64, da, dt, c);
#pragma unroll
            for (int s = 1; s < 4; s++) { wg_ss_n128_f32_bf16(acc, da + 2 * s, db + 128 * s); wg_ss_n32_f32_bf16(acc + 64, da + 2 * s, dt + 64 * s); }
            WG_COMMIT();
            WG_WAIT(1);
            mbar_arrive_if(BAR(B_QC + c - 1), lane == 0 && c > 0);
        }
        TS(34);
        mbar_wait(BAR(B_AUX));
        TS(10);
        const float2 s0 = ((const float2*)(misc + MI_STAT))[wq4 * 16 + g], s1 = ((const float2*)(misc + MI_STAT))[wq4 * 16 + g + 8];
        {
            const uint32_t sel = t == 0 ? 0x3232u : (t == 1 ? 0x4432u : 0x4444u), z = *(volatile uint32_t*)(smem + SM_ZERO);
            const uint32_t m0 = __byte_perm(__float_as_uint(-s0.x), 0, sel), m1 = __byte_perm(__float_as_uint(-s1.x), 0, sel);
            WG_FENCE();
            wg_rs_n128_f32_bf16(acc, m0, m1, z, z, mkdesc(sb + SM_MISC + MP_B, 0, 128, 0) + (hg & 2) * 16);
            wg_rs_n32_f32_bf16(acc + 64, m0, m1, z, z, mkdesc(sb + SM_MISC + MP_B, 0, 128, 0) + ((hg & 2) ? 0 : 128));
            WG_COMMIT();
        }
        WG_WAIT(1);
        mbar_arrive_e(BAR(B_QC + 8));
        const float kq = 0.23570226039551584f * 1.4426950408889634f / 512.0f;
        const float a0 = s0.y * kq, a1 = s1.y * kq;
        const uint32_t qaddr = sb + SM_A + (wq4 * 16 + (lane & 15)) * 304 + (lane >> 4) * 16;
        mbar_wait(BAR(B_QC + 8));
        WG_WAIT(0);
#pragma unroll
        for (int i = 0; i < 80; i++) asm volatile("" : "+f"(acc[i]) :: "memory");
        TS(9);
        const uint32_t qm = qaddr + (hg & 2) * 32 - (hg & 1) * 32, qe = qaddr - ((hg & 2) ? 256 : 0) - (hg & 1) * 32;
        const int skip = (0x8709 >> (4 * hg)) & 15;
#pragma unroll
        for (int s = 0; s < 10; s++) {
            const uint32_t dst = (s == 0 || s > 6) && s == skip ? sb + SM_OHI + tid * 16 : (s < 8 ? qm : qe) + s * 32;
            stsm4(dst, pk_h(acc[8*s] * a0, acc[8*s+1] * a0), pk_h(acc[8*s+2] * a1, acc[8*s+3] * a1),
                       pk_h(acc[8*s+4] * a0, acc[8*s+5] * a0), pk_h(acc[8*s+6] * a1, acc[8*s+7] * a1));
        }
        TS(43);
    } else if (warp < 13) {
        const int wi = warp - 4, R0 = cta * 16;
        const int r = 2 * wi + (lane >> 4), l = lane & 15;
        float4 a;
        {
            const int kp = wi / 3, m = wi % 3;
            const uint4* xp = (const uint4*)(P.x + (R0 + g) * DM + kp * 192) + t;
            uint4 xv[12];
#pragma unroll
            for (int i = 0; i < 12; i++) xv[i] = __ldg(xp + (i >> 1) * 4 + (i & 1) * 8 * 72);
            const bool isv = m == 1 || (m == 2 && (g & 1));
            const int wo = 72 * t + (m < 2 ? g : 8);
            const uint32_t* wp = (const uint32_t*)(smem + SM_WKV) + (isv ? 4608 : 0) + kp * 1728 + wo;
            const uint32_t* wl = kp < 2 ? wp + 1152 : (const uint32_t*)(misc + MP_W) + (isv ? 576 : 0) + wo;
            const uint32_t keep = (m == 2 && g >= 2) ? 0u : ~0u;
            uint32_t wf[48];
            float c1[4] = {0, 0, 0, 0};
            mbar_wait(BAR(B_W));
            if (wi == 0) TS(37);
#pragma unroll
            for (int s = 0; s < 12; s++) {
                const uint32_t* p = (s < 8 ? wp + (s >> 1) * 288 : wl + ((s >> 1) - 4) * 288) + (s & 1) * 36;
                const uint32_t w0 = p[0], w1 = p[9], w2 = p[18], w3 = p[27];
                wf[4*s] = (__byte_perm(w0, w1, 0x5410) & keep) | (ONE2 & ~keep); wf[4*s+1] = __byte_perm(w0, w1, 0x7632);
                wf[4*s+2] = (__byte_perm(w2, w3, 0x5410) & keep) | (ONE2 & ~keep); wf[4*s+3] = __byte_perm(w2, w3, 0x7632);
                mma_bf16(c1, wf[4*s], wf[4*s+1], wf[4*s+2], wf[4*s+3], ONE2, ONE2);
            }
            if (t == 0) *(float2*)(misc + MP_C + kp * 192 + 64 * m + 8 * g) = make_float2(c1[0], c1[2]);
            BAR_ARRIVE(8, 320);
            BAR_SYNC(9, 288);
            if (wi == 0) TS(50);
            const float zf = *(volatile float*)(smem + SM_ZERO);
            float* pk = (float*)(misc + MP_P) + kp * 640;
            const bool wr = m < 2 || g < 2;
            float ac[4][4], gr[4][4];
#pragma unroll
            for (int i = 0; i < 16; i++) { ac[i >> 2][i & 3] = zf; gr[i >> 2][i & 3] = zf; }
#pragma unroll
            for (int i = 0; i < 12; i++) {
                const int j = 8 * (i >> 1);
                mma_bf16(ac[i & 1], wf[j], wf[j+1], wf[j+2], wf[j+3], xv[i].x, xv[i].y);
                mma_bf16(ac[2 + (i & 1)], wf[j+4], wf[j+5], wf[j+6], wf[j+7], xv[i].z, xv[i].w);
            }
            const int gh = (m - kp + 3) % 3;
#pragma unroll
            for (int mm = 1; mm < 3; mm++) {
                if (gh == mm) {
#pragma unroll
                    for (int i = 6 * mm - 6; i < 6 * mm; i++) {
                        mma_bf16_k8(gr[i & 1], xv[i].x, xv[i].y, xv[i].x); mma_bf16_k8(gr[2 + (i & 1)], xv[i].x, xv[i].y, xv[i].y);
                        mma_bf16_k8(gr[i & 1], xv[i].z, xv[i].w, xv[i].z); mma_bf16_k8(gr[2 + (i & 1)], xv[i].z, xv[i].w, xv[i].w);
                    }
                }
            }
#pragma unroll
            for (int n = 0; n < 2; n++) {
                float* d = pk + (8 * n + 2 * t) * 40 + 16 * m + 2 * g;
                const float e0 = ac[n][0] + ac[2+n][0], e1 = ac[n][1] + ac[2+n][1];
                if (wr) { *(float2*)d = make_float2(e0, ac[n][2] + ac[2+n][2]); *(float2*)(d + 40) = make_float2(e1, ac[n][3] + ac[2+n][3]); }
                else if (g == 2) { d[0] = e0; d[40] = e1; }
                if (t == (g >> 1)) pk[(8 * n + g) * 40 + 37 + m] = (g & 1) ? gr[n][1] + gr[2+n][3] : gr[n][0] + gr[2+n][2];
            }
        }
        if (wi == 0) TS(12);
        BAR_SYNC(1, GATE == 1 ? 416 : 288);
        if (wi == 0) TS(38);
        if (wi < 8) {
            const float4* pa = (const float4*)(misc + MP_P) + r * 10 + min(l, 9), * pc = (const float4*)(misc + MP_C) + min(l, 8);
            const float4 u0 = pa[0], u1 = pa[160], u2 = pa[320], v0 = pc[0], v1 = pc[12], v2 = pc[24];
            a = make_float4(u0.x + u1.x + u2.x, u0.y + u1.y + u2.y, u0.z + u1.z + u2.z, u0.w + u1.w + u2.w);
            const float4 cs = make_float4(v0.x + v1.x + v2.x, v0.y + v1.y + v2.y, v0.z + v1.z + v2.z, v0.w + v1.w + v2.w);
            const float2 st = ln_stats(__shfl_sync(~0u, a.x, (lane & 16) + 9), __shfl_sync(~0u, a.y + a.z + a.w, (lane & 16) + 9));
            a.x = bfr((a.x - st.x * cs.x) * st.y); a.y = bfr((a.y - st.x * cs.y) * st.y);
            a.z = bfr((a.z - st.x * cs.z) * st.y); a.w = bfr((a.w - st.x * cs.w) * st.y);
            float n2 = a.x * a.x + a.y * a.y;
            const float n8 = __shfl_sync(~0u, n2, (lane & 16) + 8);
            n2 += a.z * a.z + a.w * a.w;
            n2 += __shfl_xor_sync(~0u, n2, 1); n2 += __shfl_xor_sync(~0u, n2, 2);
            if (l == 0) { ((float*)(misc + MP_N2))[r] = n2 + n8; ((float2*)(misc + MP_ST))[r] = st; }
            BAR_ARRIVE(6, 288);
            BAR_SYNC(3, GATE == 3 ? 384 : 256);
            if (wi == 0) TS(39);
            const uint32_t mine = ((const uint32_t*)(misc + MP_N2))[r], other = ((const uint32_t*)(misc + MP_N2))[l];
            const uint32_t bal = __ballot_sync(~0u, other > mine || (other == mine && l < r));
            const int rank = __popc((bal >> (lane & 16)) & 0xFFFFu);
            const int blk = (0x76532140u >> (4 * (rank >> 1))) & 7;
            const bool mu = rank < 4;
            const float ks = mu ? 512.f : (1.f / 512.f), vs = mu ? 128.f : -1.f;
            const float s0 = (l & 4) ? vs : ks, s1 = l < 4 ? ks : vs;
            const uint32_t w0 = nz(pk_h(a.x * s0, a.y * s0)), w1 = nz(pk_h(a.z * s1, a.w * s1));
            uint8_t* stg = misc + MP_STG + blk * 32 + (rank & 1) * 16;
            if (l < 8) {
                uint32_t* d = (uint32_t*)stg + (l < 4 ? (l >> 1) * 64 + (l & 1) * 2 : 188 + l);
                d[0] = w0; d[l < 4 ? 1 : 64] = w1;
            }
            if (l == 8) *(uint4*)(stg + 512) = make_uint4(w0, mu ? 0x5800EA00u : 0xBC002840u, 1u, w1);
            if (l == 9 && (rank & 11) == 0) ((uint32_t*)(misc + MP_INFO))[rank >> 2] = mine;
            uint32_t vm = max(__float_as_uint(fabsf(a.z)), __float_as_uint(fabsf(a.w)));
            if (l < 8) vm = max(vm, max(__float_as_uint(fabsf(a.x)), __float_as_uint(fabsf(a.y))));
            vm = __reduce_max_sync(~0u, l >= 4 && l < 9 ? vm : 0u);
            ((uint32_t*)(misc + MP_VM))[wi] = vm;
        } else {
            BAR_SYNC(6, 288);
#pragma unroll
            for (int i = 0; i < 13; i++) ((uint4*)(misc + (i < 5 ? MP_B : MI_Z - 2560)))[i * 32 + lane] = make_uint4(0, 0, 0, 0);
            BAR_SYNC(7, 160);
            delay(DLY0);
            uint4 c0[3];
            ll_load2(3, 32, c0, G->l1.csb[hg] + lane, (const uint4*)(G->l1.stat1 + qb * 64) + lane);
            TS(52);
            ((uint4*)(misc + MP_B))[(lane / 3) * 8 + lane % 3] = c0[0];
            if (lane < 28) ((uint4*)(misc + MP_B))[((lane + 32) / 3) * 8 + (lane + 32) % 3] = c0[1];
            else *(uint32_t*)(smem + SM_SW) = c0[1].x;
            ((uint4*)(misc + MI_STAT))[lane] = c0[2];
            PROXY_FENCE_SMEM();
            __syncwarp();
            mbar_arrive_e(BAR(B_AUX));
            TS(2);
        }
        if (wi < 8) {
            BAR_SYNC(4, GATE == 4 ? 384 : 256);
            if (wi == 0) {
                TS(40);
                uint4 kv[3];
#pragma unroll
                for (int it = 0; it < 3; it++) {
                    kv[it] = ((const uint4*)(misc + MP_STG))[lane + 32 * it];
                    if (it < 2 || lane < 16) st_rlx16(&G->l1.kvx[cta][lane + 32 * it], kv[it].x, kv[it].y, kv[it].z, kv[it].w);
                }
                const uint4 v = ((const uint4*)(misc + MP_ST))[lane & 7];
                if (lane < 8) st_rlx16((uint4*)(G->l1.stat1 + R0) + lane, nz(v.x), nz(v.y), nz(v.z), nz(v.w));
                TS(51);
                BAR_ARRIVE(7, 160);
#pragma unroll
                for (int it = 0; it < 3; it++) {
                    const int i = lane + 32 * it;
                    const int b = (i >> 1) & 7;
                    if (i < 80) G->kv[qb * 320 + b * 40 + (i >> 4) * 8 + 2 * ((hg + b) & 3) + (i & 1)] = kv[it];
                }
                const uint32_t vmx = __reduce_max_sync(~0u, ((const uint32_t*)(misc + MP_VM))[lane & 7]);
                if (lane < 3) red_max(&G->l1.info[lane == 1 ? cta >> 4 : 8 + (lane >> 1)], lane < 2 ? ((const uint32_t*)(misc + MP_INFO))[lane] : vmx);
            }
            if (l < 10) G->kvraw[(R0 + r) * 10 + l] = a;
        }
    } else {
        if (warp == 14) {
#pragma unroll 1
            for (int c = 7; c < 9; c++) { mbar_wait(BAR(B_QC + c - 7)); load_chunk(&tm_xw, &tm_wqt, P.x > P.wq, c, c - 2); }
        }
        if (warp == 15 && (uint32_t)__cvta_generic_to_shared(smem) != sb) __trap();
        if (warp == 13) TS(41);
    }
    const int jrot = cta >> 4;
    if (warp == 4) {
        BAR_SYNC(14, 256);
        red_release_e(&G->cnt[0]);
        TS(13);
        poll_counter(&G->cnt[0], CNT1);
        PROXY_FENCE_GMEM();
        TS(1);
        mbar_wait(BAR(B_QC + 8));
        const int t1 = (jrot + 1) & 7, t2 = (jrot + 2) & 7, n2 = min(8 - t2, 6);
        mbar_expect_e(BAR(B_KV1), 20480 + 48);
        bulk_ld_e(sb + SM_MISC + MI_KP, G->l1.info, 48, BAR(B_KV1));
        bulk_ld_e(sb + 20480, G->kv + t1 * 1280, 20480, BAR(B_KV1));
        mbar_expect_e(BAR(B_KV2), 6 * 20480);
        bulk_ld_e(sb + 2 * 20480, G->kv + t2 * 1280, n2 * 20480, BAR(B_KV2));
        if (n2 < 6) bulk_ld_e(sb + (2 + n2) * 20480, G->kv, (6 - n2) * 20480, BAR(B_KV2));
    } else if (warp > 4 && warp != 12) {
        if (warp < 12) { BAR_ARRIVE(14, 256); } else BAR_SYNC(7, 160);
        delay(DLY0);
        const int w10 = warp - 5 - (warp > 12);
        const uint4* src = G->l1.kvx[jrot * 16] + w10 * 32 + lane;
        uint4 v[4];
        const int e = w10 * 32 + lane, p = e / 80, i = e % 80, b = (i >> 1) & 7;
        ll_load(4, 320, v, src);
        mbar_wait(BAR(B_QC + 2));
#pragma unroll
        for (int j = 0; j < 4; j++) ((uint4*)smem)[j * 320 + b * 40 + (i >> 4) * 8 + 2 * ((p + b) & 3) + (i & 1)] = v[j];
        PROXY_FENCE_SMEM();
        if (warp == 5) TS(42);
    }
    if (warp != 4) { BAR_SYNC(5, 480); mbar_arrive_if(BAR(B_KV0), tid == 0); }
    else mbar_wait(BAR(B_KV0));
    if (warp == 0) { TS(11); TSG(60); }

    uint32_t ow[6];
    {
        uint32_t q[8], s[64];
        float o[12];
        load_q(q, wg);
        q[6] = *(volatile uint32_t*)(smem + SM_ZERO); q[7] = *(volatile uint32_t*)(smem + SM_ZERO);
        const uint32_t cz = POLY_CZ + q[6], ca = POLY_CA + q[6];
        uint32_t accor = 0, chk = 1, redo = 0;
        uint32_t jobs = 0x0102u | (warp == 4 ? 0x1FC00u : (warp == 8 ? 0x1E004u : (warp == 12 ? 0x1E800u : 0u)));
        int st = 0;
        WG_FENCE();
        wgz_rs_n256_f16_f16(s, q[0], q[1], q[2], q[3], mkdesc(sb, 128, 640, 0));
        wg_rs_n256_f16_f16(s, q[4], q[5], q[6], q[7], mkdesc(sb + 256, 128, 640, 0));
        WG_COMMIT();
#pragma unroll 1
        for (int it = 0;; it++) {
            if (__builtin_expect(jobs & 1, 0)) {
                const int lane = fresh_tid() & 31, t = lane & 3;
                if (it == 2) {
                    red_relaxed_e(&G->cnt[64]);
                    l2_prefetch_e(P.wg + cta * 20736, 41472); l2_prefetch_e(P.wu + cta * 20736, 41472); l2_prefetch_e(P.wd + cta * 20736, 41472);
                    tm_prefetch_e(&tm_g); tm_prefetch_e(&tm_u); tm_prefetch_e(&tm_d); tm_prefetch_e(&tm_xs); tm_prefetch_e(&tm_o);
                } else if (it != 1 && it != 8) {
                    agent_job(G, &tm_g, &tm_u, warp, st, false);
                    if (st == (0x6120 >> warp & 15)) jobs = 0;
                } else {
                    if (it == 8) {
                        float l0, l1;
                        if (check_o(o, accor, l0, l1) || redo) redo = 1;
                        else { pack_o(o, l0, l1, ow); stage_o(SM_OHI, ow); PROXY_FENCE_SMEM(); mbar_arrive_e(BAR(B_OHA)); }
                        accor = 0;
                    }
                    float n0 = sq_h2(q[0]) + sq_h2(q[2]), n1 = sq_h2(q[1]) + sq_h2(q[3]);
                    if (t == 0) { n0 += sq_h2(q[4]); n1 += sq_h2(q[5]); }
                    n0 = ((t & 2) ? n1 : n0) + __shfl_xor_sync(~0u, (t & 2) ? n0 : n1, 2);
                    n0 += __shfl_xor_sync(~0u, n0, 1);
                    const float qn = __uint_as_float(__reduce_max_sync(~0u, __float_as_uint(n0))) * 262144.0f;
                    const float kp = ((const float*)(misc + MI_KP))[lane < 8 ? (lane + jrot) & 7 : 8], vm = ((const float*)(misc + MI_KP))[9];
                    chk = __ballot_sync(~0u, !(qn * kp <= (lane < 8 ? 222.0f : 4096.0f) && fmaxf(qn, kp) <= 4096.0f && vm <= 500.0f && vm >= 0.015625f));
                    if (chk & 0x100) redo |= it == 8 ? 2 : 1;
                    chk >>= it & 1;
                }
            }
            TSL(34 + it);
            if (chk & 1) {
                WG_WAIT(0);
#pragma unroll
                for (int i = 0; i < 64; i++) asm volatile("" : "+r"(s[i]) :: "memory");
                uint32_t a4[4];
#pragma unroll
                for (int u = 0; u < 4; u++) {
                    a4[u] = or3(s[16*u+2], s[16*u+3], s[16*u+4]);
                    a4[u] = or3(a4[u], s[16*u+5], s[16*u+6]); a4[u] = or3(a4[u], s[16*u+7], s[16*u+10]);
                    a4[u] = or3(a4[u], s[16*u+11], s[16*u+12]); a4[u] = or3(a4[u], s[16*u+13], s[16*u+14]);
                }
                accor = or3(or3(accor, s[15], s[31]), or3(a4[0], s[47], s[63]), or3(a4[1], a4[2], a4[3]));
            }
            WG_WAIT(0);
#pragma unroll
            for (int i = 0; i < 64; i++) asm volatile("" : "+r"(s[i]) :: "memory");
            const uint64_t dv = mkdesc(sb + 256, 640, 128, 0) + (it & 7) * 1280;
#pragma unroll
            for (int h = 0; h < NSPLIT; h++) {
                constexpr int NR = 64 / NSPLIT;
#pragma unroll
                for (int i = h * NR; i < (h + 1) * NR; i++) s[i] = ((i >> 1) & 3) ? ex2_poly(s[i], cz, ca) : ex2_mufu(s[i]);
#pragma unroll
                for (int i = h * NR; i < (h + 1) * NR; i++) asm volatile("" : "+r"(s[i]) :: "memory");
                WG_FENCE();
#pragma unroll
                for (int c = h * NR / 4; c < (h + 1) * NR / 4; c++) {
                    if (c == 0) wgp_rs_n24_f32_f16(o, s[0], s[1], s[2], s[3], dv, it & 7);
                    else wg_rs_n24_f32_f16(o, s[4*c], s[4*c+1], s[4*c+2], s[4*c+3], dv + c * 80);
                }
            }
            WG_COMMIT();
            if (__builtin_expect((0x83 >> it) & 1, 0)) { if (it == 7) load_q(q, 4 + wg); else mbar_wait(BAR(B_KV1 + it)); }
            chk >>= 1; jobs >>= 1;
            const uint64_t dk = mkdesc(sb, 128, 640, 0) + ((it + 1) & 7) * 1280;
            WG_WAIT(0);
#pragma unroll
            for (int i = 0; i < 12; i++) asm volatile("" : "+f"(o[i]) :: "memory");
            if (it == 15) break;
            WG_FENCE();
            wgz_rs_n256_f16_f16(s, q[0], q[1], q[2], q[3], dk);
            wg_rs_n256_f16_f16(s, q[4], q[5], q[6], q[7], dk + 16);
            WG_COMMIT();
            if (it - 9u < 5u) mbar_arrive_e(BAR(B_KVD - 8 + it));
        }
        if (wq4 == 0) TS(18 + wg);
        tid = fresh_tid(); lane = tid & 31; g = lane >> 2; t = lane & 3;
        const int orow = wq4 * 16 + g;
        float l0, l1;
        if (check_o(o, accor, l0, l1)) redo |= 2;
        pack_o(o, l0, l1, ow);
        if (redo | jobs) {
            rare_finish(P, &tm_g, &tm_u, warp, st, redo);
            if (redo & 2) {
#pragma unroll
                for (int i = 0; i < 6; i++) ow[i] = G->tmp[cta][tid][i];
            }
        }
#pragma unroll
        for (int i = 0; i < 6; i++) ow[i] = nz(ow[i]);
        const uint32_t tw = __shfl_sync(~0u, ow[1], lane | 3);
        mbar_wait(BAR(B_ZOK));
        uint8_t* go = (uint8_t*)G->own[cta].o;
        const uint32_t oa1 = (2 * wg + (t >> 1)) * 1024 + orow * 16 + (t & 1) * 8;
        st_rlx8(go + oa1, ow[2], ow[4]); st_rlx8(go + oa1 + 128, ow[3], ow[5]);
        st_rlx4_if(go + 8192 + wg * 256 + (orow + (t == 2 ? 8 : 0)) * 4, t == 2 ? tw : ow[0], t >= 2);
        mbar_arrive_e(BAR(B_PUB));
        if (wq4 == 0) TS(14 + wg);
    }

    const int orow = wq4 * 16 + g;
    uint32_t wf[72];
    if (wg == 0) {
        float acc[72];
        mbar_arrive_e(BAR(B_END));
        mbar_wait(BAR(B_OHT));
        mbar_wait(BAR(B_OHA));
        TS(45); TSG(61);
        const uint4* const wo = G->wo + hg * 10368;
#define OPART(S0, N, BASE) do { WG_FENCE(); _Pragma("unroll") for (int s = 0; s < N; s++) { \
            const uint64_t da = mkdesc(sb + (S0 < 18 ? SM_OHI + (S0 + s) * 2048 : SM_OLO + (S0 + s - 18) * 2048), 1024, 128, 0); \
            const uint64_t db = mkdesc(sb + (BASE) + s * 4608, 2304, 128, 0); \
            if (S0 + s == 0) wgz_ss_n144_f32_bf16(acc, da, db); else wg_ss_n144_f32_bf16(acc, da, db); } WG_COMMIT(); } while (0)
#define OREFILL(U) do { mbar_arrive_e(BAR(B_G + U)); if (warp == 0) { mbar_wait(BAR(B_G + U)); mbar_expect_e(BAR(B_WF + 2 + U), (4 + 2 * U) * 4608); \
            bulk_ld_e(sb + (U ? SM_R : SM_A), wo + (10 + 4 * U) * 288, (4 + 2 * U) * 4608, BAR(B_WF + 2 + U)); } } while (0)
        mbar_wait(BAR(B_WF));
        OPART(0, 4, SM_A);
        OPART(4, 6, SM_R);
        WG_WAIT(1); OREFILL(0);
        WG_WAIT(0); OREFILL(1);
        mbar_wait(BAR(B_WF + 2));
        OPART(10, 4, SM_A);
        mbar_wait(BAR(B_WF + 3));
        OPART(14, 4, SM_R);
        TS(3);
        mbar_wait(BAR(B_PUB));
        stage_o(SM_OLO, ow);
        PROXY_FENCE_SMEM();
        WG_WAIT(0);
        mbar_arrive_e(BAR(B_G + 2));
        BAR_SYNC(7, 512);
        TS(22);
        OPART(18, 2, SM_R + 4 * 4608);
        mbar_wait(BAR(B_WF + 5));
        OPART(20, 8, 0);
        mbar_wait(BAR(B_WF + 6));
        OPART(28, 8, 8 * 4608);
        WG_WAIT(0);
        mbar_wait(BAR(B_XS));
#pragma unroll
        for (int i = 0; i < 72; i++) asm volatile("" : "+f"(acc[i]) :: "memory");
        TS(23);
        float sm[4] = {0, 0, 0, 0}, g1[4] = {0, 0, 0, 0}, g2[4] = {0, 0, 0, 0}, g3[4] = {0, 0, 0, 0}, g4[4] = {0, 0, 0, 0};
        const uint32_t xaddr = sb + SM_XS + (wq4 * 16 + (lane & 15)) * 304 + (lane >> 4) * 16;
        const uint8_t* wr = smem + (g == 1 ? SM_XS + 64 * 304 : SM_MISC + MI_ONE) + t * 4;
#pragma unroll
        for (int s = 0; s < 9; s++) {
            uint32_t hw[4];
            ldsm4(hw, xaddr + s * 32);
            const uint32_t w0 = *(const uint32_t*)(wr + s * 32), w1 = *(const uint32_t*)(wr + s * 32 + 16);
#pragma unroll
            for (int i = 0; i < 4; i++) hw[i] = add_bf2(hw[i], pk_bf(acc[8*s+2*i], acc[8*s+2*i+1]));
            mma_bf16(sm, hw[0], hw[1], hw[2], hw[3], w0, w1);
            mma_bf16_k8(g1, hw[0], hw[1], hw[0]); mma_bf16_k8(g2, hw[0], hw[1], hw[1]);
            mma_bf16_k8(g3, hw[2], hw[3], hw[2]); mma_bf16_k8(g4, hw[2], hw[3], hw[3]);
            stsm4(xaddr + s * 32, hw[0], hw[1], hw[2], hw[3]);
        }
        const int dl = (lane & 28) | (g >> 1);
        const float q0 = __shfl_sync(~0u, (g & 1) ? g1[1] + g3[1] : g1[0] + g3[0], dl), q1 = __shfl_sync(~0u, (g & 1) ? g2[3] + g4[3] : g2[2] + g4[2], dl);
        float4* part = G->own[cta].part + orow;
        if (t == 0) {
            st_rlx16(part, nzf(sm[0]), nzf(q0), nzf(sm[1]), 1u);
            st_rlx16(part + 8, nzf(sm[2]), nzf(q1), nzf(sm[3]), 1u);
        }
        TS(4);
        __syncwarp();
        delay(DLY1);
        const float4* pin = G->own[4 * qb + t].part + orow;
        uint4 pp[2];
        ll_load(2, 8, pp, (const uint4*)pin);
        const uint4 p0 = pp[0], p1 = pp[1];
        TS(46);
        const bool up = t & 2;
        float v0 = __uint_as_float(up ? p1.x : p0.x) + __shfl_xor_sync(~0u, __uint_as_float(up ? p0.x : p1.x), 2);
        float v1 = __uint_as_float(up ? p1.y : p0.y) + __shfl_xor_sync(~0u, __uint_as_float(up ? p0.y : p1.y), 2);
        float v2 = __uint_as_float(up ? p1.z : p0.z) + __shfl_xor_sync(~0u, __uint_as_float(up ? p0.z : p1.z), 2);
        v0 += __shfl_xor_sync(~0u, v0, 1); v1 += __shfl_xor_sync(~0u, v1, 1); v2 += __shfl_xor_sync(~0u, v2, 1);
        const float2 st = ln_stats(v0, v1);
        uint32_t u = __float_as_uint((v2 - st.x * *(const float*)(smem + SM_SW)) * st.y);
        u ^= ((int)u >> 31) | 0x80000000u;
        const int lr = orow + (t & 2) * 4;
        ((uint32_t*)(misc + MI_CS))[lr] = nz((u & 0xFFFFF800u) | (2047 - (qb * 64 + lr)));
        ((float2*)(misc + MI_STAT))[lr] = st;
        TS(24);
    } else {
        const int tl = tid & 127;
        const uint4* src = (const uint4*)G->own[4 * qb + ((hg + wg) & 3)].o + tl;
        const uint4* srct = src + 512 - (tl & 64);
        const uint32_t wa = sb + wq4 * 23040 + ((lane >> 3) & 1) * 11520 + ((lane >> 4) * 8 + (lane & 7)) * 80 + (wg - 1) * 32;
        uint4 v[5];
        mbar_wait(BAR(B_GU));
#pragma unroll
        for (int s = 0; s < 9; s++) ldsm4t(wf + 8 * s, wa + s * 1280);
        if (wg < 3) {
#pragma unroll
            for (int s = 0; s < 9; s++) ldsm4t(wf + 8 * s + 4, wa + s * 1280 + 16);
        }
        mbar_arrive_e(BAR(B_END));
        mbar_wait(BAR(warp == 15 ? B_END : B_PUB));
        if (warp == 15) {
            TS(44);
            mbar_expect_e(BAR(B_WF + 5), 8 * 4608);
            bulk_ld_e(sb, G->wo + hg * 10368 + 20 * 288, 8 * 4608, BAR(B_WF + 5));
        }
        stage_o(SM_OLO, ow);
        if (DLYO) delay(DLYO);
        ll_load2(5, 128, v, src, srct);
        uint8_t* so = smem + SM_OLO + wg * 9216;
#pragma unroll
        for (int j = 0; j < 4; j++) ((uint4*)so)[tl + j * 128] = v[j];
        if (wq4 < 2) {
            uint32_t* d = (uint32_t*)(so + 8192 + (tl & 15) * 64 + (tl >> 4) * 4);
            d[0] = v[4].x; d[4] = v[4].y; d[8] = v[4].z; d[12] = v[4].w;
        }
        if (warp == 7) {
            ((uint4*)(misc + MI_ONE))[lane] = make_uint4(ONE2, ONE2, ONE2, ONE2);
            ((uint4*)(misc + MI_ACT))[lane] = make_uint4(0, 0, 0, 0); ((uint4*)(misc + MI_ACT + 384))[lane] = make_uint4(0, 0, 0, 0);
        }
        PROXY_FENCE_SMEM();
        BAR_ARRIVE(7, 512);
        if (warp == 4) {
            mbar_wait(BAR(B_END));
            mbar_expect_e(BAR(B_WF + 6), 8 * 4608);
            bulk_ld_e(sb + 8 * 4608, G->wo + hg * 10368 + 28 * 288, 8 * 4608, BAR(B_WF + 6));
            mbar_wait(BAR(B_G + 2));
            mbar_expect_e(BAR(B_XS), 64 * 304 + 288);
            tma2d_e(sb + SM_XS, &tm_xs, hg * 144, qb * 64, BAR(B_XS));
            bulk_ld_e(sb + SM_XS + 64 * 304, P.wr + hg * 144, 288, BAR(B_XS));
            if (DNLATE) mbar_wait(BAR(B_XS));
            mbar_expect_e(BAR(B_DN), 3 * 14400);
            tma2d_e(sb + SM_DN0, &tm_d, 0, cta * 36, BAR(B_DN));
            tma2d_e(sb + SM_DN1, &tm_d, 192, cta * 36, BAR(B_DN));
            tma2d_e(sb + SM_DN2, &tm_d, 384, cta * 36, BAR(B_DN));
        }
    }
    BAR_SYNC(10, 512);

    {
        const uint32_t* keys = (const uint32_t*)(misc + MI_CS);
        const uint32_t ka = keys[lane], kb = keys[lane + 32];
        const uint4 mk = ((const uint4*)keys)[warp];
        const uint32_t my[4] = {mk.x, mk.y, mk.z, mk.w};
        uint32_t rk = 0;
#pragma unroll
        for (int i = 0; i < 4; i++) {
            const uint32_t r = __popc(__ballot_sync(~0u, ka > my[i])) + __popc(__ballot_sync(~0u, kb > my[i]));
            if (r < 8) ((uint32_t*)(misc + MI_TOP))[r] = my[i];
            rk |= r << (8 * i);
        }
        if (warp < 2) {
            BAR_SYNC(12, 512);
            const uint4 v = ((const uint4*)(misc + MI_TOP))[tid & 1];
            st_rlx16(&G->ll.top[hg * 32 + (tid >> 1)][2 * qb + (tid & 1)], v.x, v.y, v.z, v.w);
            if (warp == 0) TS(49);
        } else BAR_ARRIVE(12, 512);
#pragma unroll 1
        for (int i = 0; i < 4; i++, rk >>= 8) {
            if ((rk & 0xF8) == 0 && lane < 18) {
                const int r = 4 * warp + i;
                const uint4 v = *(const uint4*)(smem + SM_XS + r * 304 + lane * 16);
                const float2 st = ((const float2*)(misc + MI_STAT))[r];
                const uint32_t m2 = (__float_as_uint(st.x) >> 16) * 0x10001u;
                uint32_t* pn = G->ll.hn[qb][rk & 7] + hg * 72 + lane * 4;
                st_rlx16(pn, nz(ln_apply(v.x, m2, st.y)), nz(ln_apply(v.y, m2, st.y)), nz(ln_apply(v.z, m2, st.y)), nz(ln_apply(v.w, m2, st.y)));
                st_rlx16(pn + 32 * 8 * 288, nz(v.x), nz(v.y), nz(v.z), nz(v.w));
            }
        }
        __syncwarp();
    }
    uint32_t hsw = 0;
    float sgm = 0.f;
    bf16* outp = nullptr;
    if (wg == 0) {
#pragma unroll 3
        for (int it = 0; it < 9; it++) {
            const int i = it * 32 + lane, r = wq4 * 16 + i / 18, c = i % 18;
            const uint4 v = *(const uint4*)(smem + SM_XS + r * 304 + c * 16);
            const float2 st = ((const float2*)(misc + MI_STAT))[r];
            const uint32_t m2 = (__float_as_uint(st.x) >> 16) * 0x10001u;
            *(uint4*)(smem + SM_OUT + wq4 * 4608 + i * 16) = make_uint4(add_bf2(v.x, ln_apply(v.x, m2, st.y)), add_bf2(v.y, ln_apply(v.y, m2, st.y)),
                                                                       add_bf2(v.z, ln_apply(v.z, m2, st.y)), add_bf2(v.w, ln_apply(v.w, m2, st.y)));
        }
        PROXY_FENCE_SMEM();
        TS(5);
        BAR_SYNC(11, 512);
        tma2d_st_e(&tm_o, hg * 144, qb * 64 + wq4 * 16, sb + SM_OUT + wq4 * 4608);
        asm volatile("cp.async.bulk.commit_group;\ncp.async.bulk.wait_group 0;" ::: "memory");
        PROXY_FENCE_GMEM();
        TS(6);
        BAR_SYNC(9, 512);
    } else {
        if (wg > 1) {
            const int w8 = warp - 8;
            delay(DLY2);
            const uint4* ks = G->ll.top[cta] + 2 * lane;
            uint4 ab[2];
            ll_load(2, 1, ab, ks);
            uint4 a = ab[0], b = ab[1];
            if (w8 == 7) TS(25);
            uint32_t pops = 0, key = __reduce_max_sync(~0u, a.x);
#pragma unroll 1
            for (int r = 0; r < w8; r++) {
                if (a.x == key) { a.x = a.y; a.y = a.z; a.z = a.w; a.w = b.x; b.x = b.y; b.y = b.z; b.z = b.w; pops++; }
                key = __reduce_max_sync(~0u, a.x);
            }
            const int tok = 2047 - (key & 2047);
            const uint32_t slot = __shfl_sync(~0u, pops, tok >> 6);
            if (w8 == 7) TS(47);
            uint4 hv[3];
            ll_load(3, 24, hv, (const uint4*)G->ll.hn[tok >> 6][slot] + min(lane, 23));
            uint4* hd = (uint4*)(smem + SM_HN + w8 * 1168) + min(lane, 23);
            hd[0] = hv[0]; hd[24] = hv[1]; hd[48] = hv[2];
            ((uint2*)(misc + MI_SEL))[w8] = make_uint2(key, slot);
        }
        BAR_SYNC(11, OUT_LATE ? 512 : 384);
        if (warp == 4) TS(26);

        const int w12 = warp - 4;
        {
            uint32_t b[20];
#pragma unroll
            for (int i = 0; i < 5; i++) ldsm4(b + 4 * i, sb + SM_HN + (lane & 7) * 1168 + wq4 * 288 + (lane >> 3) * 16 + i * 64);
            float c[4][4];
#pragma unroll
            for (int i = 0; i < 16; i++) c[i >> 2][i & 3] = 0.f;
#pragma unroll
            for (int s = 0; s < 9; s++) {
                mma_bf16(c[s & 1], wf[8*s], wf[8*s+1], wf[8*s+2], wf[8*s+3], b[2*s], b[2*s+1]);
                mma_bf16(c[2 + (s & 1)], wf[8*s+4], wf[8*s+5], wf[8*s+6], wf[8*s+7], b[2*s], b[2*s+1]);
            }
            float4* red = (float4*)(smem + SM_RED) + wq4 * 160 + (wg - 1) * 64 + lane;
            red[0] = make_float4(c[0][0] + c[1][0], c[0][1] + c[1][1], c[0][2] + c[1][2], c[0][3] + c[1][3]);
            if (wg < 3) red[32] = make_float4(c[2][0] + c[3][0], c[2][1] + c[3][1], c[2][2] + c[3][2], c[2][3] + c[3][3]);
        }
        if (warp == 4) TS(27);
        BAR_SYNC(13, 384);
        if (w12 < 5) {
            const float4* red = (const float4*)(smem + SM_RED) + w12 * 32 + lane;
            const float4 a = red[0], b = red[160], c = red[320], d = red[480];
            const float g0 = bfr((a.x + b.x) + (c.x + d.x)), g1 = bfr((a.y + b.y) + (c.y + d.y));
            const float u0 = bfr((a.z + b.z) + (c.z + d.z)), u1 = bfr((a.w + b.w) + (c.w + d.w));
            const float y0 = bfr(g0 * frcp(1.0f + __expf(-g0))) * u0, y1 = bfr(g1 * frcp(1.0f + __expf(-g1))) * u1;
            const int f = 8 * w12 + g - (cta & 1) * 4;
            if (f >= 0 && f < 36) {
                bf16* act = (bf16*)(misc + MI_ACT);
                act[(2 * t) * 56 + f] = __float2bfloat16_rn(y0);
                act[(2 * t + 1) * 56 + f] = __float2bfloat16_rn(y1);
            }
        }
        mbar_wait(BAR(B_DN));
        {
            const int mat = lane >> 3, r = lane & 7;
#pragma unroll
            for (int i = 0; i < 9; i++)
                ldsm4t(wf + 4 * i, sb + (i < 3 ? SM_DN0 : (i < 6 ? SM_DN1 : SM_DN2)) + min(16 * (i % 3) + (mat >> 1) * 8 + r, 35) * 400 + (16 * w12 + (mat & 1) * 8) * 2);
        }
        if (warp == 4) TS(48);
        BAR_SYNC(9, 512);
        if (warp == 4) TS(28);
        {
            uint32_t b[6];
#pragma unroll
            for (int i = 0; i < 6; i++) b[i] = *(const uint32_t*)(misc + MI_ACT + g * 112 + i * 16 + t * 4);
            float c[3][4];
#pragma unroll
            for (int i = 0; i < 12; i++) c[i >> 2][i & 3] = 0.f;
#pragma unroll
            for (int i = 0; i < 9; i++) { const int it = i % 3, s = i / 3, j = 12 * it + 4 * s; mma_bf16(c[it], wf[j], wf[j+1], wf[j+2], wf[j+3], b[2*s], b[2*s+1]); }
#pragma unroll
            for (int it = 0; it < 3; it++) {
                uint32_t* yp = &G->ll.y[2 * (w12 + 12 * it)][cta][lane];
                st_rlx4(yp, nz(pk_bf(c[it][0], c[it][1])));
                st_rlx4(yp + NCTA * 32, nz(pk_bf(c[it][2], c[it][3])));
            }
        }
        if (warp == 4) TS(29);
        if (warp < 6 && cta < 72) {
            const int e = tid & 63;
            const uint2 sel = ((const uint2*)(misc + MI_SEL))[e & 7];
            const uint32_t* hp = G->ll.hs[(2047 - (sel.x & 2047)) >> 6][sel.y] + cta * 4 + (e >> 4);
            uint32_t u = (sel.x & 0xFFFFF800u) | 0x400u;
            u ^= (~(int)u >> 31) | 0x80000000u;
            sgm = bfr(frcp(1.0f + __expf(-bfr(__uint_as_float(u)))));
            outp = P.out + (2047 - (sel.x & 2047)) * DM + cta * 8 + (e >> 3);
            hsw = ll_load4(hp);
            const uint32_t hnw = ((const uint32_t*)(smem + SM_HN + (e & 7) * 1168))[cta * 4 + (e >> 4)];
            hsw = (e & 8) ? __byte_perm(hsw, hnw, 0x7632) : __byte_perm(hsw, hnw, 0x5410);
        }
    }
    if (cta < 72) {
        if (warp < 4 || warp > 5) delay(warp < 4 ? DLY3 + 250 : DLY3);
        const uint4* src = (const uint4*)G->ll.y[cta] + tid;
        uint4 vv[2];
        ll_load(2, 512, vv, src);
        const uint4 va = vv[0], vb = vv[1];
        float s[8] = {bf_lo(va.x) + bf_lo(vb.x), bf_hi(va.x) + bf_hi(vb.x), bf_lo(va.y) + bf_lo(vb.y), bf_hi(va.y) + bf_hi(vb.y),
                      bf_lo(va.z) + bf_lo(vb.z), bf_hi(va.z) + bf_hi(vb.z), bf_lo(va.w) + bf_lo(vb.w), bf_hi(va.w) + bf_hi(vb.w)};
        const bool u4 = lane & 16, u2 = lane & 8;
#pragma unroll
        for (int i = 0; i < 4; i++) s[i] = (u4 ? s[i + 4] : s[i]) + __shfl_xor_sync(~0u, u4 ? s[i] : s[i + 4], 16);
#pragma unroll
        for (int i = 0; i < 2; i++) s[i] = (u2 ? s[i + 2] : s[i]) + __shfl_xor_sync(~0u, u2 ? s[i] : s[i + 2], 8);
        *(float2*)(misc + MI_Z + warp * 256 + (lane & 7) * 32 + (lane >> 3) * 8) = make_float2(s[0], s[1]);
        BAR_SYNC(8, 512);
        if (warp == 4) TS(30);
        if (warp == 4 || warp == 5) {
            const int e = tid & 63;
            float y = 0.f;
#pragma unroll
            for (int w = 0; w < 16; w++) y += ((const float*)(misc + MI_Z))[w * 64 + e];
            *outp = __float2bfloat16_rn(bf_lo(hsw) + bfr(bf_hi(hsw) + bfr(bfr(y) * sgm)));
        }
        if (cta == 0 && tid < NCTA + NHELP) G->oflag[tid][0] = 0;
    }
    if (warp == 4) { TS(31); TSG(33); }
    MARK(99999);
}

typedef CUresult (*EncodeFn)(CUtensorMap*, CUtensorMapDataType, cuuint32_t, void*, const cuuint64_t*, const cuuint64_t*,
                             const cuuint32_t*, const cuuint32_t*, CUtensorMapInterleave, CUtensorMapSwizzle,
                             CUtensorMapL2promotion, CUtensorMapFloatOOBfill);

static void make_map(EncodeFn enc, CUtensorMap* tm, const void* p, int cols, int rows, int bc, int br, CUtensorMapSwizzle sw) {
    cuuint64_t gd[2] = {(cuuint64_t)cols, (cuuint64_t)rows}, gs[1] = {(cuuint64_t)cols * 2};
    cuuint32_t bx[2] = {(cuuint32_t)bc, (cuuint32_t)br}, es[2] = {1, 1};
    enc(tm, CU_TENSOR_MAP_DATA_TYPE_BFLOAT16, 2, (void*)p, gd, gs, bx, es, CU_TENSOR_MAP_INTERLEAVE_NONE, sw,
        CU_TENSOR_MAP_L2_PROMOTION_L2_128B, CU_TENSOR_MAP_FLOAT_OOB_FILL_NONE);
}

extern "C" void kernel_launch(void* const* d_in, const int* in_sizes, int n_in, void* d_out, int out_size) {
    static EncodeFn enc = nullptr;
    static void* scratch = nullptr;
    if (!enc) {
        void* fn = nullptr;
        cudaDriverEntryPointQueryResult qr;
        cudaGetDriverEntryPoint("cuTensorMapEncodeTiled", &fn, cudaEnableDefault, &qr);
        enc = (EncodeFn)fn;
        cudaGetSymbolAddress(&scratch, g_scratch);
        cudaFuncSetAttribute(fused_block, cudaFuncAttributeMaxDynamicSharedMemorySize, SM_TOTAL);
    }
    Params P;
    P.g = (Scratch*)scratch;
    P.x = (const bf16*)d_in[0]; P.wq = (const bf16*)d_in[1]; P.wk = (const bf16*)d_in[2]; P.wv = (const bf16*)d_in[3];
    P.wo = (const bf16*)d_in[4]; P.wr = (const bf16*)d_in[6]; P.wg = (const bf16*)d_in[7]; P.wu = (const bf16*)d_in[8];
    P.wd = (const bf16*)d_in[9]; P.out = (bf16*)d_out;
    CUtensorMap txw, twqt, tg, tu, txs, td, to;
    {
        const char* lo = (const char*)(P.x > P.wq ? P.wq : P.x);
        const char* hi = (const char*)(P.x > P.wq ? P.x : P.wq);
        cuuint64_t gd[3] = {DM, SEQ, 2}, gs[2] = {DM * 2, (cuuint64_t)(hi - lo)};
        cuuint32_t bx[3] = {64, 64, 1}, es[3] = {1, 1, 1};
        enc(&txw, CU_TENSOR_MAP_DATA_TYPE_BFLOAT16, 3, (void*)lo, gd, gs, bx, es, CU_TENSOR_MAP_INTERLEAVE_NONE, CU_TENSOR_MAP_SWIZZLE_128B,
            CU_TENSOR_MAP_L2_PROMOTION_L2_128B, CU_TENSOR_MAP_FLOAT_OOB_FILL_NONE);
    }
    make_map(enc, &twqt, P.wq, DM, DM, 32, 64, CU_TENSOR_MAP_SWIZZLE_64B);
    make_map(enc, &tg, P.wg, FF, DM, 40, 144, CU_TENSOR_MAP_SWIZZLE_NONE);
    make_map(enc, &tu, P.wu, FF, DM, 40, 144, CU_TENSOR_MAP_SWIZZLE_NONE);
    make_map(enc, &txs, P.x, DM, SEQ, 152, 64, CU_TENSOR_MAP_SWIZZLE_NONE);
    make_map(enc, &td, P.wd, DM, FF, 200, 36, CU_TENSOR_MAP_SWIZZLE_NONE);
    make_map(enc, &to, P.out, DM, SEQ, 144, 16, CU_TENSOR_MAP_SWIZZLE_NONE);
    fused_block<<<NCTA + NHELP, NTHR, SM_TOTAL, cudaStreamPerThread>>>(P, txw, twqt, tg, tu, txs, td, to);
}
```

```cpp
#include <cuda_runtime.h>
#include <cuda_bf16.h>
#include <cuda_fp16.h>
#include <cuda.h>
#include <stdint.h>

#define POLY_DEG3 0

__device__ __forceinline__ void wgz_rs_n256_f16_f16(uint32_t* d, uint32_t a0, uint32_t a1, uint32_t a2, uint32_t a3, uint64_t db) {
  asm volatile("{\n.reg .pred p;\nsetp.ne.b32 p, 0, 0;\n"
    "wgmma.mma_async.sync.aligned.m64n256k16.f16.f16.f16 "
    "{%0,%1,%2,%3,%4,%5,%6,%7,%8,%9,%10,%11,%12,%13,%14,%15,%16,%17,%18,%19,%20,%21,%22,%23,%24,%25,%26,%27,%28,%29,%30,%31,%32,%33,%34,%35,%36,%37,%38,%39,%40,%41,%42,%43,%44,%45,%46,%47,%48,%49,%50,%51,%52,%53,%54,%55,%56,%57,%58,%59,%60,%61,%62,%63}, "
    "{%64,%65,%66,%67}, %68, p, 1, 1, 0;\n}\n"
    : "=r"(d[0]), "=r"(d[1]), "=r"(d[2]), "=r"(d[3]), "=r"(d[4]), "=r"(d[5]), "=r"(d[6]), "=r"(d[7]),
      "=r"(d[8]), "=r"(d[9]), "=r"(d[10]), "=r"(d[11]), "=r"(d[12]), "=r"(d[13]), "=r"(d[14]), "=r"(d[15]),
      "=r"(d[16]), "=r"(d[17]), "=r"(d[18]), "=r"(d[19]), "=r"(d[20]), "=r"(d[21]), "=r"(d[22]), "=r"(d[23]),
      "=r"(d[24]), "=r"(d[25]), "=r"(d[26]), "=r"(d[27]), "=r"(d[28]), "=r"(d[29]), "=r"(d[30]), "=r"(d[31]),
      "=r"(d[32]), "=r"(d[33]), "=r"(d[34]), "=r"(d[35]), "=r"(d[36]), "=r"(d[37]), "=r"(d[38]), "=r"(d[39]),
      "=r"(d[40]), "=r"(d[41]), "=r"(d[42]), "=r"(d[43]), "=r"(d[44]), "=r"(d[45]), "=r"(d[46]), "=r"(d[47]),
      "=r"(d[48]), "=r"(d[49]), "=r"(d[50]), "=r"(d[51]), "=r"(d[52]), "=r"(d[53]), "=r"(d[54]), "=r"(d[55]),
      "=r"(d[56]), "=r"(d[57]), "=r"(d[58]), "=r"(d[59]), "=r"(d[60]), "=r"(d[61]), "=r"(d[62]), "=r"(d[63])
    : "r"(a0), "r"(a1), "r"(a2), "r"(a3), "l"(db));
}
__device__ __forceinline__ void wg_rs_n256_f16_f16(uint32_t* d, uint32_t a0, uint32_t a1, uint32_t a2, uint32_t a3, uint64_t db) {
  asm volatile("{\n.reg .pred p;\nsetp.ne.b32 p, 1, 0;\n"
    "wgmma.mma_async.sync.aligned.m64n256k16.f16.f16.f16 "
    "{%0,%1,%2,%3,%4,%5,%6,%7,%8,%9,%10,%11,%12,%13,%14,%15,%16,%17,%18,%19,%20,%21,%22,%23,%24,%25,%26,%27,%28,%29,%30,%31,%32,%33,%34,%35,%36,%37,%38,%39,%40,%41,%42,%43,%44,%45,%46,%47,%48,%49,%50,%51,%52,%53,%54,%55,%56,%57,%58,%59,%60,%61,%62,%63}, "
    "{%64,%65,%66,%67}, %68, p, 1, 1, 0;\n}\n"
    : "+r"(d[0]), "+r"(d[1]), "+r"(d[2]), "+r"(d[3]), "+r"(d[4]), "+r"(d[5]), "+r"(d[6]), "+r"(d[7]),
      "+r"(d[8]), "+r"(d[9]), "+r"(d[10]), "+r"(d[11]), "+r"(d[12]), "+r"(d[13]), "+r"(d[14]), "+r"(d[15]),
      "+r"(d[16]), "+r"(d[17]), "+r"(d[18]), "+r"(d[19]), "+r"(d[20]), "+r"(d[21]), "+r"(d[22]), "+r"(d[23]),
      "+r"(d[24]), "+r"(d[25]), "+r"(d[26]), "+r"(d[27]), "+r"(d[28]), "+r"(d[29]), "+r"(d[30]), "+r"(d[31]),
      "+r"(d[32]), "+r"(d[33]), "+r"(d[34]), "+r"(d[35]), "+r"(d[36]), "+r"(d[37]), "+r"(d[38]), "+r"(d[39]),
      "+r"(d[40]), "+r"(d[41]), "+r"(d[42]), "+r"(d[43]), "+r"(d[44]), "+r"(d[45]), "+r"(d[46]), "+r"(d[47]),
      "+r"(d[48]), "+r"(d[49]), "+r"(d[50]), "+r"(d[51]), "+r"(d[52]), "+r"(d[53]), "+r"(d[54]), "+r"(d[55]),
      "+r"(d[56]), "+r"(d[57]), "+r"(d[58]), "+r"(d[59]), "+r"(d[60]), "+r"(d[61]), "+r"(d[62]), "+r"(d[63])
    : "r"(a0), "r"(a1), "r"(a2), "r"(a3), "l"(db));
}
__device__ __forceinline__ void wg_rs_n24_f32_f16(float* d, uint32_t a0, uint32_t a1, uint32_t a2, uint32_t a3, uint64_t db) {
  asm volatile("{\n.reg .pred p;\nsetp.ne.b32 p, 1, 0;\n"
    "wgmma.mma_async.sync.aligned.m64n24k16.f32.f16.f16 "
    "{%0,%1,%2,%3,%4,%5,%6,%7,%8,%9,%10,%11}, "
    "{%12,%13,%14,%15}, %16, p, 1, 1, 1;\n}\n"
    : "+f"(d[0]), "+f"(d[1]), "+f"(d[2]), "+f"(d[3]), "+f"(d[4]), "+f"(d[5]), "+f"(d[6]), "+f"(d[7]),
      "+f"(d[8]), "+f"(d[9]), "+f"(d[10]), "+f"(d[11])
    : "r"(a0), "r"(a1), "r"(a2), "r"(a3), "l"(db));
}
__device__ __forceinline__ void wgp_rs_n24_f32_f16(float* d, uint32_t a0, uint32_t a1, uint32_t a2, uint32_t a3, uint64_t db, uint32_t sd) {
  asm volatile("{\n.reg .pred p;\nsetp.ne.b32 p, %17, 0;\n"
    "wgmma.mma_async.sync.aligned.m64n24k16.f32.f16.f16 "
    "{%0,%1,%2,%3,%4,%5,%6,%7,%8,%9,%10,%11}, "
    "{%12,%13,%14,%15}, %16, p, 1, 1, 1;\n}\n"
    : "+f"(d[0]), "+f"(d[1]), "+f"(d[2]), "+f"(d[3]), "+f"(d[4]), "+f"(d[5]), "+f"(d[6]), "+f"(d[7]),
      "+f"(d[8]), "+f"(d[9]), "+f"(d[10]), "+f"(d[11])
    : "r"(a0), "r"(a1), "r"(a2), "r"(a3), "l"(db), "r"(sd));
}
__device__ __forceinline__ void wgp_ss_n128_f32_bf16(float* d, uint64_t da, uint64_t db, uint32_t sd) {
  asm volatile("{\n.reg .pred p;\nsetp.ne.b32 p, %66, 0;\n"
    "wgmma.mma_async.sync.aligned.m64n128k16.f32.bf16.bf16 "
    "{%0,%1,%2,%3,%4,%5,%6,%7,%8,%9,%10,%11,%12,%13,%14,%15,%16,%17,%18,%19,%20,%21,%22,%23,%24,%25,%26,%27,%28,%29,%30,%31,%32,%33,%34,%35,%36,%37,%38,%39,%40,%41,%42,%43,%44,%45,%46,%47,%48,%49,%50,%51,%52,%53,%54,%55,%56,%57,%58,%59,%60,%61,%62,%63}, "
    "%64, %65, p, 1, 1, 0, 1;\n}\n"
    : "+f"(d[0]), "+f"(d[1]), "+f"(d[2]), "+f"(d[3]), "+f"(d[4]), "+f"(d[5]), "+f"(d[6]), "+f"(d[7]),
      "+f"(d[8]), "+f"(d[9]), "+f"(d[10]), "+f"(d[11]), "+f"(d[12]), "+f"(d[13]), "+f"(d[14]), "+f"(d[15]),
      "+f"(d[16]), "+f"(d[17]), "+f"(d[18]), "+f"(d[19]), "+f"(d[20]), "+f"(d[21]), "+f"(d[22]), "+f"(d[23]),
      "+f"(d[24]), "+f"(d[25]), "+f"(d[26]), "+f"(d[27]), "+f"(d[28]), "+f"(d[29]), "+f"(d[30]), "+f"(d[31]),
      "+f"(d[32]), "+f"(d[33]), "+f"(d[34]), "+f"(d[35]), "+f"(d[36]), "+f"(d[37]), "+f"(d[38]), "+f"(d[39]),
      "+f"(d[40]), "+f"(d[41]), "+f"(d[42]), "+f"(d[43]), "+f"(d[44]), "+f"(d[45]), "+f"(d[46]), "+f"(d[47]),
      "+f"(d[48]), "+f"(d[49]), "+f"(d[50]), "+f"(d[51]), "+f"(d[52]), "+f"(d[53]), "+f"(d[54]), "+f"(d[55]),
      "+f"(d[56]), "+f"(d[57]), "+f"(d[58]), "+f"(d[59]), "+f"(d[60]), "+f"(d[61]), "+f"(d[62]), "+f"(d[63])
    : "l"(da), "l"(db), "r"(sd));
}
__device__ __forceinline__ void wg_ss_n128_f32_bf16(float* d, uint64_t da, uint64_t db) {
  asm volatile("{\n.reg .pred p;\nsetp.ne.b32 p, 1, 0;\n"
    "wgmma.mma_async.sync.aligned.m64n128k16.f32.bf16.bf16 "
    "{%0,%1,%2,%3,%4,%5,%6,%7,%8,%9,%10,%11,%12,%13,%14,%15,%16,%17,%18,%19,%20,%21,%22,%23,%24,%25,%26,%27,%28,%29,%30,%31,%32,%33,%34,%35,%36,%37,%38,%39,%40,%41,%42,%43,%44,%45,%46,%47,%48,%49,%50,%51,%52,%53,%54,%55,%56,%57,%58,%59,%60,%61,%62,%63}, "
    "%64, %65, p, 1, 1, 0, 1;\n}\n"
    : "+f"(d[0]), "+f"(d[1]), "+f"(d[2]), "+f"(d[3]), "+f"(d[4]), "+f"(d[5]), "+f"(d[6]), "+f"(d[7]),
      "+f"(d[8]), "+f"(d[9]), "+f"(d[10]), "+f"(d[11]), "+f"(d[12]), "+f"(d[13]), "+f"(d[14]), "+f"(d[15]),
      "+f"(d[16]), "+f"(d[17]), "+f"(d[18]), "+f"(d[19]), "+f"(d[20]), "+f"(d[21]), "+f"(d[22]), "+f"(d[23]),
      "+f"(d[24]), "+f"(d[25]), "+f"(d[26]), "+f"(d[27]), "+f"(d[28]), "+f"(d[29]), "+f"(d[30]), "+f"(d[31]),
      "+f"(d[32]), "+f"(d[33]), "+f"(d[34]), "+f"(d[35]), "+f"(d[36]), "+f"(d[37]), "+f"(d[38]), "+f"(d[39]),
      "+f"(d[40]), "+f"(d[41]), "+f"(d[42]), "+f"(d[43]), "+f"(d[44]), "+f"(d[45]), "+f"(d[46]), "+f"(d[47]),
      "+f"(d[48]), "+f"(d[49]), "+f"(d[50]), "+f"(d[51]), "+f"(d[52]), "+f"(d[53]), "+f"(d[54]), "+f"(d[55]),
      "+f"(d[56]), "+f"(d[57]), "+f"(d[58]), "+f"(d[59]), "+f"(d[60]), "+f"(d[61]), "+f"(d[62]), "+f"(d[63])
    : "l"(da), "l"(db));
}
__device__ __forceinline__ void wgp_ss_n32_f32_bf16(float* d, uint64_t da, uint64_t db, uint32_t sd) {
  asm volatile("{\n.reg .pred p;\nsetp.ne.b32 p, %18, 0;\n"
    "wgmma.mma_async.sync.aligned.m64n32k16.f32.bf16.bf16 "
    "{%0,%1,%2,%3,%4,%5,%6,%7,%8,%9,%10,%11,%12,%13,%14,%15}, "
    "%16, %17, p, 1, 1, 0, 1;\n}\n"
    : "+f"(d[0]), "+f"(d[1]), "+f"(d[2]), "+f"(d[3]), "+f"(d[4]), "+f"(d[5]), "+f"(d[6]), "+f"(d[7]),
      "+f"(d[8]), "+f"(d[9]), "+f"(d[10]), "+f"(d[11]), "+f"(d[12]), "+f"(d[13]), "+f"(d[14]), "+f"(d[15])
    : "l"(da), "l"(db), "r"(sd));
}
__device__ __forceinline__ void wg_ss_n32_f32_bf16(float* d, uint64_t da, uint64_t db) {
  asm volatile("{\n.reg .pred p;\nsetp.ne.b32 p, 1, 0;\n"
    "wgmma.mma_async.sync.aligned.m64n32k16.f32.bf16.bf16 "
    "{%0,%1,%2,%3,%4,%5,%6,%7,%8,%9,%10,%11,%12,%13,%14,%15}, "
    "%16, %17, p, 1, 1, 0, 1;\n}\n"
    : "+f"(d[0]), "+f"(d[1]), "+f"(d[2]), "+f"(d[3]), "+f"(d[4]), "+f"(d[5]), "+f"(d[6]), "+f"(d[7]),
      "+f"(d[8]), "+f"(d[9]), "+f"(d[10]), "+f"(d[11]), "+f"(d[12]), "+f"(d[13]), "+f"(d[14]), "+f"(d[15])
    : "l"(da), "l"(db));
}
__device__ __forceinline__ void wg_rs_n128_f32_bf16(float* d, uint32_t a0, uint32_t a1, uint32_t a2, uint32_t a3, uint64_t db) {
  asm volatile("{\n.reg .pred p;\nsetp.ne.b32 p, 1, 0;\n"
    "wgmma.mma_async.sync.aligned.m64n128k16.f32.bf16.bf16 "
    "{%0,%1,%2,%3,%4,%5,%6,%7,%8,%9,%10,%11,%12,%13,%14,%15,%16,%17,%18,%19,%20,%21,%22,%23,%24,%25,%26,%27,%28,%29,%30,%31,%32,%33,%34,%35,%36,%37,%38,%39,%40,%41,%42,%43,%44,%45,%46,%47,%48,%49,%50,%51,%52,%53,%54,%55,%56,%57,%58,%59,%60,%61,%62,%63}, "
    "{%64,%65,%66,%67}, %68, p, 1, 1, 1;\n}\n"
    : "+f"(d[0]), "+f"(d[1]), "+f"(d[2]), "+f"(d[3]), "+f"(d[4]), "+f"(d[5]), "+f"(d[6]), "+f"(d[7]),
      "+f"(d[8]), "+f"(d[9]), "+f"(d[10]), "+f"(d[11]), "+f"(d[12]), "+f"(d[13]), "+f"(d[14]), "+f"(d[15]),
      "+f"(d[16]), "+f"(d[17]), "+f"(d[18]), "+f"(d[19]), "+f"(d[20]), "+f"(d[21]), "+f"(d[22]), "+f"(d[23]),
      "+f"(d[24]), "+f"(d[25]), "+f"(d[26]), "+f"(d[27]), "+f"(d[28]), "+f"(d[29]), "+f"(d[30]), "+f"(d[31]),
      "+f"(d[32]), "+f"(d[33]), "+f"(d[34]), "+f"(d[35]), "+f"(d[36]), "+f"(d[37]), "+f"(d[38]), "+f"(d[39]),
      "+f"(d[40]), "+f"(d[41]), "+f"(d[42]), "+f"(d[43]), "+f"(d[44]), "+f"(d[45]), "+f"(d[46]), "+f"(d[47]),
      "+f"(d[48]), "+f"(d[49]), "+f"(d[50]), "+f"(d[51]), "+f"(d[52]), "+f"(d[53]), "+f"(d[54]), "+f"(d[55]),
      "+f"(d[56]), "+f"(d[57]), "+f"(d[58]), "+f"(d[59]), "+f"(d[60]), "+f"(d[61]), "+f"(d[62]), "+f"(d[63])
    : "r"(a0), "r"(a1), "r"(a2), "r"(a3), "l"(db));
}
__device__ __forceinline__ void wgp_rs_n128_f32_bf16(float* d, uint32_t a0, uint32_t a1, uint32_t a2, uint32_t a3, uint64_t db, uint32_t sd) {
  asm volatile("{\n.reg .pred p;\nsetp.ne.b32 p, %69, 0;\n"
    "wgmma.mma_async.sync.aligned.m64n128k16.f32.bf16.bf16 "
    "{%0,%1,%2,%3,%4,%5,%6,%7,%8,%9,%10,%11,%12,%13,%14,%15,%16,%17,%18,%19,%20,%21,%22,%23,%24,%25,%26,%27,%28,%29,%30,%31,%32,%33,%34,%35,%36,%37,%38,%39,%40,%41,%42,%43,%44,%45,%46,%47,%48,%49,%50,%51,%52,%53,%54,%55,%56,%57,%58,%59,%60,%61,%62,%63}, "
    "{%64,%65,%66,%67}, %68, p, 1, 1, 1;\n}\n"
    : "+f"(d[0]), "+f"(d[1]), "+f"(d[2]), "+f"(d[3]), "+f"(d[4]), "+f"(d[5]), "+f"(d[6]), "+f"(d[7]),
      "+f"(d[8]), "+f"(d[9]), "+f"(d[10]), "+f"(d[11]), "+f"(d[12]), "+f"(d[13]), "+f"(d[14]), "+f"(d[15]),
      "+f"(d[16]), "+f"(d[17]), "+f"(d[18]), "+f"(d[19]), "+f"(d[20]), "+f"(d[21]), "+f"(d[22]), "+f"(d[23]),
      "+f"(d[24]), "+f"(d[25]), "+f"(d[26]), "+f"(d[27]), "+f"(d[28]), "+f"(d[29]), "+f"(d[30]), "+f"(d[31]),
      "+f"(d[32]), "+f"(d[33]), "+f"(d[34]), "+f"(d[35]), "+f"(d[36]), "+f"(d[37]), "+f"(d[38]), "+f"(d[39]),
      "+f"(d[40]), "+f"(d[41]), "+f"(d[42]), "+f"(d[43]), "+f"(d[44]), "+f"(d[45]), "+f"(d[46]), "+f"(d[47]),
      "+f"(d[48]), "+f"(d[49]), "+f"(d[50]), "+f"(d[51]), "+f"(d[52]), "+f"(d[53]), "+f"(d[54]), "+f"(d[55]),
      "+f"(d[56]), "+f"(d[57]), "+f"(d[58]), "+f"(d[59]), "+f"(d[60]), "+f"(d[61]), "+f"(d[62]), "+f"(d[63])
    : "r"(a0), "r"(a1), "r"(a2), "r"(a3), "l"(db), "r"(sd));
}
__device__ __forceinline__ void wgp_rs_n32_f32_bf16(float* d, uint32_t a0, uint32_t a1, uint32_t a2, uint32_t a3, uint64_t db, uint32_t sd) {
  asm volatile("{\n.reg .pred p;\nsetp.ne.b32 p, %21, 0;\n"
    "wgmma.mma_async.sync.aligned.m64n32k16.f32.bf16.bf16 "
    "{%0,%1,%2,%3,%4,%5,%6,%7,%8,%9,%10,%11,%12,%13,%14,%15}, "
    "{%16,%17,%18,%19}, %20, p, 1, 1, 1;\n}\n"
    : "+f"(d[0]), "+f"(d[1]), "+f"(d[2]), "+f"(d[3]), "+f"(d[4]), "+f"(d[5]), "+f"(d[6]), "+f"(d[7]),
      "+f"(d[8]), "+f"(d[9]), "+f"(d[10]), "+f"(d[11]), "+f"(d[12]), "+f"(d[13]), "+f"(d[14]), "+f"(d[15])
    : "r"(a0), "r"(a1), "r"(a2), "r"(a3), "l"(db), "r"(sd));
}
__device__ __forceinline__ void wg_rs_n32_f32_bf16(float* d, uint32_t a0, uint32_t a1, uint32_t a2, uint32_t a3, uint64_t db) {
  asm volatile("{\n.reg .pred p;\nsetp.ne.b32 p, 1, 0;\n"
    "wgmma.mma_async.sync.aligned.m64n32k16.f32.bf16.bf16 "
    "{%0,%1,%2,%3,%4,%5,%6,%7,%8,%9,%10,%11,%12,%13,%14,%15}, "
    "{%16,%17,%18,%19}, %20, p, 1, 1, 1;\n}\n"
    : "+f"(d[0]), "+f"(d[1]), "+f"(d[2]), "+f"(d[3]), "+f"(d[4]), "+f"(d[5]), "+f"(d[6]), "+f"(d[7]),
      "+f"(d[8]), "+f"(d[9]), "+f"(d[10]), "+f"(d[11]), "+f"(d[12]), "+f"(d[13]), "+f"(d[14]), "+f"(d[15])
    : "r"(a0), "r"(a1), "r"(a2), "r"(a3), "l"(db));
}
__device__ __forceinline__ void wgz_ss_n144_f32_bf16(float* d, uint64_t da, uint64_t db) {
  asm volatile("{\n.reg .pred p;\nsetp.ne.b32 p, 0, 0;\n"
    "wgmma.mma_async.sync.aligned.m64n144k16.f32.bf16.bf16 "
    "{%0,%1,%2,%3,%4,%5,%6,%7,%8,%9,%10,%11,%12,%13,%14,%15,%16,%17,%18,%19,%20,%21,%22,%23,%24,%25,%26,%27,%28,%29,%30,%31,%32,%33,%34,%35,%36,%37,%38,%39,%40,%41,%42,%43,%44,%45,%46,%47,%48,%49,%50,%51,%52,%53,%54,%55,%56,%57,%58,%59,%60,%61,%62,%63,%64,%65,%66,%67,%68,%69,%70,%71}, "
    "%72, %73, p, 1, 1, 0, 1;\n}\n"
    : "=f"(d[0]), "=f"(d[1]), "=f"(d[2]), "=f"(d[3]), "=f"(d[4]), "=f"(d[5]), "=f"(d[6]), "=f"(d[7]),
      "=f"(d[8]), "=f"(d[9]), "=f"(d[10]), "=f"(d[11]), "=f"(d[12]), "=f"(d[13]), "=f"(d[14]), "=f"(d[15]),
      "=f"(d[16]), "=f"(d[17]), "=f"(d[18]), "=f"(d[19]), "=f"(d[20]), "=f"(d[21]), "=f"(d[22]), "=f"(d[23]),
      "=f"(d[24]), "=f"(d[25]), "=f"(d[26]), "=f"(d[27]), "=f"(d[28]), "=f"(d[29]), "=f"(d[30]), "=f"(d[31]),
      "=f"(d[32]), "=f"(d[33]), "=f"(d[34]), "=f"(d[35]), "=f"(d[36]), "=f"(d[37]), "=f"(d[38]), "=f"(d[39]),
      "=f"(d[40]), "=f"(d[41]), "=f"(d[42]), "=f"(d[43]), "=f"(d[44]), "=f"(d[45]), "=f"(d[46]), "=f"(d[47]),
      "=f"(d[48]), "=f"(d[49]), "=f"(d[50]), "=f"(d[51]), "=f"(d[52]), "=f"(d[53]), "=f"(d[54]), "=f"(d[55]),
      "=f"(d[56]), "=f"(d[57]), "=f"(d[58]), "=f"(d[59]), "=f"(d[60]), "=f"(d[61]), "=f"(d[62]), "=f"(d[63]),
      "=f"(d[64]), "=f"(d[65]), "=f"(d[66]), "=f"(d[67]), "=f"(d[68]), "=f"(d[69]), "=f"(d[70]), "=f"(d[71])
    : "l"(da), "l"(db));
}
__device__ __forceinline__ void wg_ss_n144_f32_bf16(float* d, uint64_t da, uint64_t db) {
  asm volatile("{\n.reg .pred p;\nsetp.ne.b32 p, 1, 0;\n"
    "wgmma.mma_async.sync.aligned.m64n144k16.f32.bf16.bf16 "
    "{%0,%1,%2,%3,%4,%5,%6,%7,%8,%9,%10,%11,%12,%13,%14,%15,%16,%17,%18,%19,%20,%21,%22,%23,%24,%25,%26,%27,%28,%29,%30,%31,%32,%33,%34,%35,%36,%37,%38,%39,%40,%41,%42,%43,%44,%45,%46,%47,%48,%49,%50,%51,%52,%53,%54,%55,%56,%57,%58,%59,%60,%61,%62,%63,%64,%65,%66,%67,%68,%69,%70,%71}, "
    "%72, %73, p, 1, 1, 0, 1;\n}\n"
    : "+f"(d[0]), "+f"(d[1]), "+f"(d[2]), "+f"(d[3]), "+f"(d[4]), "+f"(d[5]), "+f"(d[6]), "+f"(d[7]),
      "+f"(d[8]), "+f"(d[9]), "+f"(d[10]), "+f"(d[11]), "+f"(d[12]), "+f"(d[13]), "+f"(d[14]), "+f"(d[15]),
      "+f"(d[16]), "+f"(d[17]), "+f"(d[18]), "+f"(d[19]), "+f"(d[20]), "+f"(d[21]), "+f"(d[22]), "+f"(d[23]),
      "+f"(d[24]), "+f"(d[25]), "+f"(d[26]), "+f"(d[27]), "+f"(d[28]), "+f"(d[29]), "+f"(d[30]), "+f"(d[31]),
      "+f"(d[32]), "+f"(d[33]), "+f"(d[34]), "+f"(d[35]), "+f"(d[36]), "+f"(d[37]), "+f"(d[38]), "+f"(d[39]),
      "+f"(d[40]), "+f"(d[41]), "+f"(d[42]), "+f"(d[43]), "+f"(d[44]), "+f"(d[45]), "+f"(d[46]), "+f"(d[47]),
      "+f"(d[48]), "+f"(d[49]), "+f"(d[50]), "+f"(d[51]), "+f"(d[52]), "+f"(d[53]), "+f"(d[54]), "+f"(d[55]),
      "+f"(d[56]), "+f"(d[57]), "+f"(d[58]), "+f"(d[59]), "+f"(d[60]), "+f"(d[61]), "+f"(d[62]), "+f"(d[63]),
      "+f"(d[64]), "+f"(d[65]), "+f"(d[66]), "+f"(d[67]), "+f"(d[68]), "+f"(d[69]), "+f"(d[70]), "+f"(d[71])
    : "l"(da), "l"(db));
}

typedef __nv_bfloat16 bf16;
constexpr int SEQ = 2048, DM = 576, FF = 4608;
constexpr int NCTA = 128, NHELP = 4, NTHR = 512;

struct LLScratch {
    uint32_t y[72][NCTA][32];
    uint32_t hn[32][8][288];
    uint32_t hs[32][8][288];
    uint4    top[NCTA][64];
};
static_assert(sizeof(LLScratch) % (NHELP * 16) == 0, "zero slices");
struct LLOwn {
    uint32_t o[2304];
    float4   part[64];
};
struct LLFirst {
    uint4 kvx[NCTA][80];
    float2 stat1[SEQ];
    uint32_t info[32];
    uint4 csb[4][64];
};
struct Scratch {
    LLScratch ll;
    LLFirst l1;
    LLOwn own[NCTA];
    uint4 kv[SEQ * 5];
    uint4 o1[NCTA][576];
    uint4 wo[4 * 36 * 288];
    float4 kvraw[SEQ * 10];
    uint32_t tmp[NCTA][NTHR][8];
    uint32_t flag[32][32];
    uint32_t cnt[96];
};
__device__ __align__(1024) Scratch g_scratch;
constexpr uint32_t CNT1 = NCTA;

#define TS(i)
#define TSG(i)
#define TSL(i)

constexpr int SM_X = 147456;
constexpr int SM_WKV = 61440;
constexpr int SM_OLO = 126976, SM_OHI = 163840;
constexpr int SM_A = 200704;
constexpr int SM_R = 92160;
constexpr int SM_XS = SM_OHI;
constexpr int SM_DN0 = SM_OHI + 20096, SM_DN1 = 73728, SM_DN2 = SM_A;
constexpr int SM_OUT = SM_OLO;
constexpr int SM_HN = 0, SM_RED = 9344;
constexpr int SM_MISC = 221184;
constexpr int SM_BAR = SM_MISC + 10752;
constexpr int SM_TOTAL = 232448;
constexpr int MP_C = 512, MP_N2 = 1088, MP_ST = 1152, MP_VM = 1280, MP_INFO = 1312, MP_P = 2304, MP_STG = 2304, MP_B = 3584, MP_W = 5888;
constexpr int MI_STAT = 0;
constexpr int MI_CS = 512;
constexpr int MI_KP = 1088;
constexpr int MI_TOP = 1152;
constexpr int MI_FL = 1184;
constexpr int MI_ACT = 1344;
constexpr int MI_SEL = 2304;
constexpr int MI_ONE = 2560;
constexpr int MI_Z = 6400;
constexpr int SM_SW = SM_TOTAL - 16;
constexpr int SM_ZERO = SM_TOTAL - 8;
enum { B_KV1 = 0, B_KV2, B_FL, B_AUX = 4, B_ZOK, B_OHT, B_XS, B_DN, B_GU, B_FULL = 10, B_WF = 19, B_KV0 = 27,
       B_G = 28, B_QC = 31, B_PUB = 40, B_OHA, B_END, B_W = 44, B_NUM };
static_assert(B_NUM * 8 <= SM_TOTAL - SM_BAR, "barriers");

constexpr uint32_t sb = 1024;
#define BAR(i) (sb + SM_BAR + 8 * (i))

#define MARK(x)
#define MARKMASK 0
#define WG_FENCE() asm volatile("wgmma.fence.sync.aligned;" ::: "memory")
#define WG_COMMIT() asm volatile("wgmma.commit_group.sync.aligned;" ::: "memory")
#define WG_WAIT(n) asm volatile("wgmma.wait_group.sync.aligned %0;" :: "n"(n) : "memory")
#define BAR_SYNC(id, n) asm volatile("barrier.cta.sync %0, %1;" :: "n"(id), "n"(n) : "memory")
#define BAR_ARRIVE(id, n) asm volatile("barrier.cta.arrive %0, %1;" :: "n"(id), "n"(n) : "memory")
#define PROXY_FENCE_GMEM() asm volatile("fence.proxy.async.global;" ::: "memory")
#define PROXY_FENCE_SMEM() asm volatile("fence.proxy.async.shared::cta;" ::: "memory")

__device__ __forceinline__ constexpr uint64_t mkdesc(uint32_t addr, uint32_t lbo, uint32_t sbo, uint32_t mode) {
    return (uint64_t)((addr & 0x3FFFF) >> 4) | ((uint64_t)(lbo >> 4) << 16) | ((uint64_t)(sbo >> 4) << 32) | ((uint64_t)mode << 62);
}
#define ELECT "{\n.reg .pred e;\nelect.sync _|e, 0xffffffff;\n@e "
__device__ __forceinline__ void mbar_init_e(uint32_t b, int c) { asm volatile(ELECT "mbarrier.init.shared::cta.b64 [%0], %1;\n}" :: "r"(b), "r"(c) : "memory"); }
__device__ __forceinline__ void mbar_expect_e(uint32_t b, uint32_t tx) { asm volatile(ELECT "mbarrier.arrive.expect_tx.shared::cta.b64 _, [%0], %1;\n}" :: "r"(b), "r"(tx) : "memory"); }
__device__ __forceinline__ void mbar_arrive_e(uint32_t b) { asm volatile(ELECT "mbarrier.arrive.shared::cta.b64 _, [%0];\n}" :: "r"(b) : "memory"); }
__device__ __forceinline__ void mbar_arrive_if(uint32_t b, bool c) {
    asm volatile("{.reg .pred p; setp.ne.u32 p, %1, 0; @p mbarrier.arrive.shared::cta.b64 _, [%0];}" :: "r"(b), "r"((uint32_t)c) : "memory");
}
__device__ __forceinline__ bool mbar_test(uint32_t b) {
    uint32_t ok;
    asm volatile("{.reg .pred p; mbarrier.test_wait.parity.shared::cta.b64 p, [%1], 0; selp.u32 %0, 1, 0, p;}" : "=r"(ok) : "r"(b) : "memory");
    return __all_sync(~0u, ok);
}
#define GIVEUP(n) "@!p st.shared.u32 [c], c;\n"
#define LIMIT "0x400000"
#define WAITFN template <int LN> __device__ __forceinline__
#define SPIN_HEAD "{\n.reg .pred p, q;\n.reg .u32 c, v;\nmov.u32 c, 0;\nW: .pragma \"nounroll\";\n"
#define SPIN_TAIL(n) "add.u32 c, c, 1;\nsetp.lt.and.u32 q, c, " LIMIT ", !p;\n@q bra.uni W;\n" GIVEUP(n) "}"
WAITFN void mbar_wait_(uint32_t b) {
    asm volatile(SPIN_HEAD "mbarrier.try_wait.parity.shared::cta.b64 p, [%0], 0;\n" SPIN_TAIL(1) :: "r"(b), "n"(LN) : "memory");
}
#define mbar_wait(b) mbar_wait_<__LINE__>(b)
__device__ __forceinline__ void bulk_ld_e(uint32_t dst, const void* src, uint32_t bytes, uint32_t bar) {
    asm volatile(ELECT "cp.async.bulk.shared::cluster.global.mbarrier::complete_tx::bytes [%0], [%1], %2, [%3];\n}"
                 :: "r"(dst), "l"(src), "r"(bytes), "r"(bar) : "memory");
}
__device__ __forceinline__ void bulk_st_e(void* dst, uint32_t src, uint32_t bytes) {
    asm volatile(ELECT "cp.async.bulk.global.shared::cta.bulk_group [%0], [%1], %2;\n}" :: "l"(dst), "r"(src), "r"(bytes) : "memory");
}
__device__ __forceinline__ void tma2d_e(uint32_t dst, const CUtensorMap* tm, int c0, int c1, uint32_t bar) {
    asm volatile(ELECT "cp.async.bulk.tensor.2d.shared::cluster.global.mbarrier::complete_tx::bytes [%0], [%1, {%3, %4}], [%2];\n}"
                 :: "r"(dst), "l"(tm), "r"(bar), "r"(c0), "r"(c1) : "memory");
}
__device__ __forceinline__ void tma3d_e(uint32_t dst, const CUtensorMap* tm, int c0, int c1, int c2, uint32_t bar) {
    asm volatile(ELECT "cp.async.bulk.tensor.3d.shared::cluster.global.mbarrier::complete_tx::bytes [%0], [%1, {%3, %4, %5}], [%2];\n}"
                 :: "r"(dst), "l"(tm), "r"(bar), "r"(c0), "r"(c1), "r"(c2) : "memory");
}
__device__ __forceinline__ void tma4d_e(uint32_t dst, const CUtensorMap* tm, int c0, int c1, int c2, int c3, uint32_t bar) {
    asm volatile(ELECT "cp.async.bulk.tensor.4d.shared::cluster.global.mbarrier::complete_tx::bytes [%0], [%1, {%3, %4, %5, %6}], [%2];\n}"
                 :: "r"(dst), "l"(tm), "r"(bar), "r"(c0), "r"(c1), "r"(c2), "r"(c3) : "memory");
}
__device__ __forceinline__ void tma2d_st_e(const CUtensorMap* tm, int c0, int c1, uint32_t src) {
    asm volatile(ELECT "cp.async.bulk.tensor.2d.global.shared::cta.bulk_group [%0, {%2, %3}], [%1];\n}" :: "l"(tm), "r"(src), "r"(c0), "r"(c1) : "memory");
}
__device__ __forceinline__ void l2_prefetch_e(const void* src, uint32_t bytes) {
    asm volatile(ELECT "cp.async.bulk.prefetch.L2.global [%0], %1;\n}" :: "l"(src), "r"(bytes) : "memory");
}
__device__ __forceinline__ void tm_prefetch_e(const CUtensorMap* tm) { asm volatile(ELECT "prefetch.tensormap [%0];\n}" :: "l"(tm) : "memory"); }
__device__ __forceinline__ void red_release_e(uint32_t* p) { asm volatile(ELECT "red.release.gpu.global.add.u32 [%0], 1;\n}" :: "l"(p) : "memory"); }
__device__ __forceinline__ void red_max(uint32_t* p, uint32_t v) { asm volatile("red.relaxed.gpu.global.max.u32 [%0], %1;" :: "l"(p), "r"(v) : "memory"); }
__device__ __forceinline__ void red_relaxed_e(uint32_t* p) { asm volatile(ELECT "red.relaxed.gpu.global.add.u32 [%0], 1;\n}" :: "l"(p) : "memory"); }
WAITFN void poll_counter_(const uint32_t* p, uint32_t target) {
    asm volatile(SPIN_HEAD "ld.acquire.gpu.global.u32 v, [%0];\nsetp.ge.u32 p, v, %1;\n" SPIN_TAIL(2) :: "l"(p), "r"(target), "n"(LN) : "memory");
}
#define poll_counter(p, t) poll_counter_<__LINE__>(p, t)
__device__ __forceinline__ uint4 ld_rlx16(const void* p) {
    uint4 v;
    asm volatile("ld.relaxed.gpu.global.v4.u32 {%0,%1,%2,%3}, [%4];" : "=r"(v.x), "=r"(v.y), "=r"(v.z), "=r"(v.w) : "l"(p) : "memory");
    return v;
}
__device__ __forceinline__ uint32_t ld_rlx4(const void* p) {
    uint32_t v;
    asm volatile("ld.relaxed.gpu.global.u32 %0, [%1];" : "=r"(v) : "l"(p) : "memory");
    return v;
}
template <int LN, int NA, int SA, int NB, int SB> __device__ __forceinline__ void ll_load_ab(uint4* v, const uint4* pa, const uint4* pb) {
    constexpr int N = NA + NB;
    uint32_t c = 0, again;
#pragma unroll 1
    do {
        uint32_t m = ~0u;
#pragma unroll
        for (int i = 0; i < N; i++) v[i] = ld_rlx16(i < NA ? pa + i * SA : pb + (i - NA) * SB);
#pragma unroll
        for (int i = 0; i < N; i++) m = min(min(m, v[i].x), min(min(v[i].y, v[i].z), v[i].w));
        c++;
        asm volatile("{\n.reg .pred p, q;\n.reg .u32 c;\nmov.u32 c, %1;\nsetp.lt.u32 p, c, " LIMIT ";\nsetp.eq.and.u32 q, %2, 0, p;\nselp.u32 %0, 1, 0, q;\n" GIVEUP(3) "}"
                     : "=r"(again) : "r"(c), "r"(m), "n"(LN) : "memory");
    } while (__any_sync(~0u, again));
}
#define ll_load(N, S, v, p) ll_load_ab<__LINE__, N, S, 0, 0>(v, p, nullptr)
#define ll_load2(N, S, v, p, plast) ll_load_ab<__LINE__, (N) - 1, S, 1, 0>(v, p, plast)
WAITFN uint32_t ll_load4_(const void* p) {
    uint32_t r;
    asm volatile(SPIN_HEAD "ld.relaxed.gpu.global.u32 %0, [%1];\nsetp.ne.u32 q, %0, 0;\nvote.sync.all.pred p, q, 0xffffffff;\n" SPIN_TAIL(2)
                 : "=&r"(r) : "l"(p), "n"(LN) : "memory");
    return r;
}
#define ll_load4(p) ll_load4_<__LINE__>(p)
__device__ __forceinline__ void st_rlx4(void* p, uint32_t a) { asm volatile("st.relaxed.gpu.global.u32 [%0], %1;" :: "l"(p), "r"(a) : "memory"); }
__device__ __forceinline__ void st_rlx4_if(void* p, uint32_t a, bool c) {
    asm volatile("{.reg .pred p; setp.ne.u32 p, %2, 0; @p st.relaxed.gpu.global.u32 [%0], %1;}" :: "l"(p), "r"(a), "r"((uint32_t)c) : "memory");
}
__device__ __forceinline__ void st_rlx16_if(void* p, uint32_t a, uint32_t b, uint32_t c, uint32_t d, bool e) {
    asm volatile("{.reg .pred p; setp.ne.u32 p, %5, 0; @p st.relaxed.gpu.global.v4.u32 [%0], {%1,%2,%3,%4};}" :: "l"(p), "r"(a), "r"(b), "r"(c), "r"(d), "r"((uint32_t)e) : "memory");
}
__device__ __forceinline__ void st_rlx8(void* p, uint32_t a, uint32_t b) { asm volatile("st.relaxed.gpu.global.v2.u32 [%0], {%1,%2};" :: "l"(p), "r"(a), "r"(b) : "memory"); }
__device__ __forceinline__ void st_rlx16(void* p, uint32_t a, uint32_t b, uint32_t c, uint32_t d) {
    asm volatile("st.relaxed.gpu.global.v4.u32 [%0], {%1,%2,%3,%4};" :: "l"(p), "r"(a), "r"(b), "r"(c), "r"(d) : "memory");
}
__device__ __forceinline__ uint32_t nz(uint32_t w) { uint32_t r; asm("max.u32 %0, %1, 1;" : "=r"(r) : "r"(w)); return r; }
__device__ __forceinline__ uint32_t nzf(float f) { return nz(__float_as_uint(f)); }
__device__ __forceinline__ void mma_bf16(float* d, uint32_t a0, uint32_t a1, uint32_t a2, uint32_t a3, uint32_t b0, uint32_t b1) {
    asm volatile("mma.sync.aligned.m16n8k16.row.col.f32.bf16.bf16.f32 {%0,%1,%2,%3}, {%4,%5,%6,%7}, {%8,%9}, {%0,%1,%2,%3};"
                 : "+f"(d[0]), "+f"(d[1]), "+f"(d[2]), "+f"(d[3]) : "r"(a0), "r"(a1), "r"(a2), "r"(a3), "r"(b0), "r"(b1));
}
__device__ __forceinline__ void mma_bf16_k8(float* d, uint32_t a0, uint32_t a1, uint32_t b0) {
    asm volatile("mma.sync.aligned.m16n8k8.row.col.f32.bf16.bf16.f32 {%0,%1,%2,%3}, {%4,%5}, {%6}, {%0,%1,%2,%3};"
                 : "+f"(d[0]), "+f"(d[1]), "+f"(d[2]), "+f"(d[3]) : "r"(a0), "r"(a1), "r"(b0));
}
__device__ __forceinline__ void delay(uint32_t cyc) {
    asm volatile("{\n.reg .pred p;\n.reg .u32 c, c0;\nmov.u32 c0, %%clock;\nW: .pragma \"nounroll\";\nmov.u32 c, %%clock;\nsub.u32 c, c, c0;\n"
                 "setp.lt.u32 p, c, %0;\n@p bra.uni W;\n}" :: "r"(cyc) : "memory");
}
__device__ __forceinline__ int fresh_cta() { int v; asm volatile("mov.u32 %0, %%ctaid.x;" : "=r"(v)); return v - NHELP; }
__device__ __forceinline__ int fresh_tid() { int v; asm volatile("mov.u32 %0, %%tid.x;" : "=r"(v)); return v; }
__device__ __forceinline__ void ldsm4(uint32_t* r, uint32_t a) {
    asm volatile("ldmatrix.sync.aligned.m8n8.x4.shared.b16 {%0,%1,%2,%3}, [%4];" : "=r"(r[0]), "=r"(r[1]), "=r"(r[2]), "=r"(r[3]) : "r"(a) : "memory");
}
__device__ __forceinline__ void ldsm4t(uint32_t* r, uint32_t a) {
    asm volatile("ldmatrix.sync.aligned.m8n8.x4.trans.shared.b16 {%0,%1,%2,%3}, [%4];" : "=r"(r[0]), "=r"(r[1]), "=r"(r[2]), "=r"(r[3]) : "r"(a) : "memory");
}
__device__ __forceinline__ void stsm4(uint32_t a, uint32_t r0, uint32_t r1, uint32_t r2, uint32_t r3) {
    asm volatile("stmatrix.sync.aligned.m8n8.x4.shared.b16 [%0], {%1,%2,%3,%4};" :: "r"(a), "r"(r0), "r"(r1), "r"(r2), "r"(r3) : "memory");
}
__device__ __forceinline__ float frcp(float x) { float r; asm("rcp.approx.ftz.f32 %0, %1;" : "=f"(r) : "f"(x)); return r; }
__device__ __forceinline__ float fsqrt(float x) { float r; asm("sqrt.approx.ftz.f32 %0, %1;" : "=f"(r) : "f"(x)); return r; }
__device__ __forceinline__ float bfr(float x) { uint32_t r; asm("cvt.rn.bf16x2.f32 %0, %1, %2;" : "=r"(r) : "f"(x), "f"(0.f)); return __uint_as_float(r); }
__device__ __forceinline__ float sigmoidf(float x) { float e; asm("ex2.approx.ftz.f32 %0, %1;" : "=f"(e) : "f"(x * -1.4426950408889634f)); return frcp(1.0f + e); }
__device__ __forceinline__ uint32_t pk_bf(float lo, float hi) { uint32_t r; asm("cvt.rn.bf16x2.f32 %0, %1, %2;" : "=r"(r) : "f"(hi), "f"(lo)); return r; }
__device__ __forceinline__ uint32_t pk_h(float lo, float hi) { uint32_t r; asm("cvt.rn.f16x2.f32 %0, %1, %2;" : "=r"(r) : "f"(hi), "f"(lo)); return r; }
__device__ __forceinline__ float bf_lo(uint32_t w) { return __uint_as_float(w << 16); }
__device__ __forceinline__ float bf_hi(uint32_t w) { return __uint_as_float(w & 0xFFFF0000u); }
__device__ __forceinline__ uint32_t add_bf2(uint32_t a, uint32_t b) { uint32_t r; asm("add.rn.bf16x2 %0, %1, %2;" : "=r"(r) : "r"(a), "r"(b)); return r; }
__device__ __forceinline__ uint32_t sub_bf2(uint32_t a, uint32_t b) { uint32_t r; asm("sub.rn.bf16x2 %0, %1, %2;" : "=r"(r) : "r"(a), "r"(b)); return r; }
__device__ __forceinline__ float2 ln_stats(float sx, float sxx) {
    float mean = sx * (1.0f / DM);
    float var = fmaxf(sxx * (1.0f / DM) - mean * mean, 0.0f);
    float s = bfr(fsqrt(bfr(bfr(var) + 1e-5f)));
    return make_float2(bfr(mean), frcp(s));
}
__device__ __forceinline__ uint32_t ln_apply(uint32_t w, uint32_t m2, float inv) {
    uint32_t d = sub_bf2(w, m2);
    return pk_bf(bf_lo(d) * inv, bf_hi(d) * inv);
}

__device__ __forceinline__ uint32_t ex2_mufu(uint32_t v) { uint32_t r; asm("ex2.approx.f16x2 %0, %1;" : "=r"(r) : "r"(v)); return r; }
__device__ __forceinline__ uint32_t hfma2(uint32_t a, uint32_t b, uint32_t c) { uint32_t r; asm("fma.rn.f16x2 %0, %1, %2, %3;" : "=r"(r) : "r"(a), "r"(b), "r"(c)); return r; }
__device__ __forceinline__ uint32_t ex2_poly(uint32_t w, uint32_t ca, bool alu) {
    const uint32_t e = alu ? __funnelshift_l(w, w, 4) : w * 16;
    const uint32_t q = hfma2(w & 0x003F003Fu, ca, 0x98B498B4u);
    return e + hfma2(q, q, 0x03A903A9u);
}
constexpr uint32_t POLY_CA = POLY_DEG3 ? 0x6DFA6DFAu : 0x64A064A0u;
#define MUMASK 0x1111
constexpr __host__ __device__ uint32_t blk_table(uint32_t m) {
    uint32_t t = 0, n = 0;
    for (int pass = 1; pass >= 0; pass--) for (uint32_t b = 0; b < 8; b++) if ((int)((m >> b) & 1) == pass) t |= b << (4 * n++);
    return t;
}
constexpr __host__ __device__ int popc8(uint32_t m) { int n = 0; for (int b = 0; b < 8; b++) n += (m >> b) & 1; return n; }

struct Params {
    Scratch* g;
    const bf16 *x, *wk, *wv, *wq, *wo, *wr, *wg, *wu, *wd;
    bf16* out;
};

extern __shared__ __align__(1024) uint8_t smem_dyn[];
#define smem ((uint8_t*)__cvta_shared_to_generic(sb))

__device__ __forceinline__ void attn_safe(const Scratch* G, const bf16* x, const bf16* wq, int row0, int head, uint32_t* res) {
    const int lane = threadIdx.x & 31, half = lane & 1, row = row0 + (lane >> 1);
    const float2 st = ((const float2*)(smem + SM_MISC + MI_STAT))[row & 63];
    float q[18];
#pragma unroll
    for (int d = 0; d < 18; d++) q[d] = 0.f;
#pragma unroll 1
    for (int i = half * 288; i < half * 288 + 288; i++) {
        float xn = bfr(bfr(__bfloat162float(x[row * DM + i]) - st.x) * st.y);
#pragma unroll
        for (int d = 0; d < 18; d++) q[d] += xn * __bfloat162float(wq[i * DM + head * 18 + d]);
    }
#pragma unroll
    for (int d = 0; d < 18; d++) q[d] = bfr(q[d] + __shfl_xor_sync(~0u, q[d], 1)) * 0.23570226039551584f;
    float o[18], l = 0.f, m = -INFINITY;
#pragma unroll
    for (int d = 0; d < 18; d++) o[d] = 0.f;
#pragma unroll 1
    for (int pass = 0; pass < 2; pass++) {
#pragma unroll 1
        for (int k = half * 1024; k < half * 1024 + 1024; k++) {
            const float4* p = G->kvraw + k * 10;
            float4 e = __ldcg(p + 8);
            float s = q[16] * e.x + q[17] * e.y;
#pragma unroll
            for (int j = 0; j < 4; j++) { float4 a = __ldcg(p + j); s += q[4*j] * a.x + q[4*j+1] * a.y + q[4*j+2] * a.z + q[4*j+3] * a.w; }
            if (pass == 0) { m = fmaxf(m, s); }
            else {
                float pr = __expf(s - m);
                l += pr; o[16] += pr * e.z; o[17] += pr * e.w;
#pragma unroll
                for (int j = 0; j < 4; j++) { float4 a = __ldcg(p + 4 + j); o[4*j] += pr * a.x; o[4*j+1] += pr * a.y; o[4*j+2] += pr * a.z; o[4*j+3] += pr * a.w; }
            }
        }
        if (pass == 0) m = fmaxf(m, __shfl_xor_sync(~0u, m, 1));
    }
    l += __shfl_xor_sync(~0u, l, 1);
    const float inv = frcp(l);
    const int g = lane >> 2, t = lane & 3;
#pragma unroll
    for (int p = 0; p < 9; p++) {
        float a = o[2*p] + __shfl_xor_sync(~0u, o[2*p], 1), b = o[2*p+1] + __shfl_xor_sync(~0u, o[2*p+1], 1);
        uint32_t w = pk_bf(a * inv, b * inv);
        uint32_t v0 = __shfl_sync(~0u, w, 2 * g), v1 = __shfl_sync(~0u, w, 2 * g + 16);
        if (p == 2 * t) { res[2] = v0; res[3] = v1; }
        if (p == 2 * t + 1) { res[4] = v0; res[5] = v1; }
        if (p == 8) { res[0] = v0; res[1] = v1; }
    }
}

#define NSPLIT 1
#define XAT 3
#define DNLATE 4
#define IMADMOD 2
#define DLYS 500
#define LBO2 0
#define NHOLD 5
#define QRS 1
#define DLY0 400
#define DLYO 0
#define DLY1 100
#define DLY2 900
#define DLY3 500

__device__ __forceinline__ void job_store_o1(Scratch* G, int cta) {
    PROXY_FENCE_SMEM();
    bulk_st_e(G->o1[cta], sb + SM_OHI + (cta & 3) * 9216, 9216);
    asm volatile("cp.async.bulk.commit_group;" ::: "memory");
}
__device__ __forceinline__ void job_flag_o1(Scratch* G, int cta) {
    asm volatile("cp.async.bulk.wait_group 0;" ::: "memory");
    PROXY_FENCE_GMEM();
    red_relaxed_e(&G->flag[cta >> 2][cta & 3]);
}
__device__ __forceinline__ void job_load_o1(Scratch* G, int cta) {
    mbar_arrive_e(BAR(B_ZOK));
    mbar_expect_e(BAR(B_OHT), 4 * 9216);
    bulk_ld_e(sb + SM_OHI, G->o1[cta & ~3], 4 * 9216, BAR(B_OHT));
}
__device__ __forceinline__ void job_load_wo(Scratch* G, int cta, int u) {
    mbar_expect_e(BAR(B_WF + u), (2 + u) * 9216);
    bulk_ld_e(sb + (u ? SM_R : SM_A), G->wo + (cta & 3) * 10368 + u * 1152, (2 + u) * 9216, BAR(B_WF + u));
}

__device__ __forceinline__ void load_q(uint32_t* q, int head, int tid) {
    const int t = tid & 3;
    const uint8_t* qs = smem + SM_A + (((tid >> 5) & 3) * 16 + ((tid & 31) >> 2)) * 304 + head * 36;
    q[0] = *(const uint32_t*)(qs + 4 * t); q[1] = *(const uint32_t*)(qs + 8 * 304 + 4 * t);
    q[2] = *(const uint32_t*)(qs + 16 + 4 * t); q[3] = *(const uint32_t*)(qs + 8 * 304 + 16 + 4 * t);
    q[4] = *(const uint32_t*)(qs + 32); q[5] = *(const uint32_t*)(qs + 8 * 304 + 32);
    const uint32_t sel = 0x66666654u >> (t == 1 ? 0 : 16) ^ (t == 0 ? 0x5476u : 0u);
    q[4] = __byte_perm(q[4], 0x1800u, sel); q[5] = __byte_perm(q[5], 0x1800u, sel);
}
__device__ __forceinline__ bool check_o(const float* o, uint32_t accor, float& l0, float& l1, int tid) {
    const int src = ((tid & 28) | 1);
    l0 = __shfl_sync(~0u, o[1], src); l1 = __shfl_sync(~0u, o[3], src);
    return __any_sync(~0u, max(accor >> 16, accor & 0xFFFFu) >= 30 * 64 || !(fminf(l0, l1) >= 8.0f && l0 + l1 <= 1e30f));
}
__device__ __forceinline__ void pack_o(const float* o, float l0, float l1, uint32_t* ow) {
    const float i0 = frcp(l0), i1 = frcp(l1);
#pragma unroll
    for (int i = 0; i < 6; i++) ow[i] = pk_bf(o[2*i] * ((i & 1) ? i1 : i0), o[2*i+1] * ((i & 1) ? i1 : i0));
}
__device__ __forceinline__ void stage_o(int base, const uint32_t* ow, int tid) {
    const int t = tid & 3, wg = tid >> 7;
    uint8_t* so = smem + base + (((tid >> 5) & 3) * 16 + ((tid & 31) >> 2)) * 16;
    uint8_t* s1 = so + (2 * wg + (t >> 1)) * 1024 + (t & 1) * 8;
    *(uint2*)s1 = make_uint2(ow[2], ow[4]); *(uint2*)(s1 + 128) = make_uint2(ow[3], ow[5]);
    if (t == 3) { *(uint32_t*)(so + 8192 + wg * 4) = ow[0]; *(uint32_t*)(so + 8320 + wg * 4) = ow[1]; }
}

__device__ __noinline__ void rare_finish(const Params& P, int warp, uint32_t redo) {
    Scratch* const G = P.g;
    const int cta = blockIdx.x - NHELP;
    warp = __shfl_sync(~0u, warp, 0); redo = __shfl_sync(~0u, redo, 0);
#pragma unroll 1
    for (int r = 0; r < 2; r++) {
        if ((redo >> r) & 1) {
            uint32_t res[6];
            attn_safe(G, P.x, P.wq, (cta >> 2) * 64 + (warp & 3) * 16, (cta & 3) * 8 + 4 * r + (warp >> 2), res);
            if (r == 0) { stage_o(SM_OHI + (cta & 3) * 9216, res, threadIdx.x); __syncwarp(); mbar_arrive_e(BAR(B_OHA)); }
            else {
#pragma unroll
                for (int i = 0; i < 6; i++) G->tmp[cta][threadIdx.x][i] = res[i];
            }
        }
    }
    if (redo & 4) { mbar_wait(BAR(B_OHA)); job_store_o1(G, cta); job_flag_o1(G, cta); }
    if (redo & 8) { ll_load4(&G->flag[cta >> 2][threadIdx.x & 7]); PROXY_FENCE_GMEM(); job_load_o1(G, cta); }
    if (redo & 16) { mbar_wait(BAR(B_ZOK)); job_load_wo(G, cta, warp == 1); }
}

__device__ __forceinline__ void load_chunk(const CUtensorMap* tm_xw, const CUtensorMap* tm_wqt, int xi, int c, int sl) {
    const int hg = blockIdx.x & 3, w0 = (9 * hg >> 1) * 32;
    const uint32_t slot = sb + sl * 20480, bar = BAR(B_FULL + c);
    tma3d_e(slot, tm_xw, w0 + (hg & 2) * 16, c * 64, xi ^ 1, bar);
    tma3d_e(slot + 8192, tm_xw, w0 + (hg & 2) * 16 + 64, c * 64, xi ^ 1, bar);
    tma2d_e(slot + 16384, tm_wqt, w0 + ((hg & 2) ? 0 : 128), c * 64, bar);
}

__device__ __forceinline__ void helper(const Params& P, const CUtensorMap* tm_xw, const CUtensorMap* tm_wqt, int warp) {
    Scratch* const G = P.g;
    const int hb = blockIdx.x, tid = threadIdx.x, lane = tid & 31, g = lane >> 2, t = lane & 3;
    constexpr int HZ = 184320, HB = HZ + 32768;
    if (warp < 4) {
        float acc[80];
        uint32_t on[4];
#pragma unroll
        for (int i = 0; i < 4; i++) on[i] = 0x3F803F80u + *(volatile uint32_t*)(smem + SM_ZERO);
#pragma unroll 1
        for (int c = 0; c < 9; c++) {
            const uint64_t db = mkdesc(sb, 8192, 1024, 1) + c * 1280, dt = mkdesc(sb + 16384, 512, 512, 2) + c * 1280;
            mbar_wait(BAR(B_FULL + c));
            WG_FENCE();
            wgp_rs_n128_f32_bf16(acc, on[0], on[1], on[2], on[3], db, c); wgp_rs_n32_f32_bf16(acc + 64, on[0], on[1], on[2], on[3], dt, c);
#pragma unroll
            for (int s = 1; s < 4; s++) { wg_rs_n128_f32_bf16(acc, on[0], on[1], on[2], on[3], db + 128 * s); wg_rs_n32_f32_bf16(acc + 64, on[0], on[1], on[2], on[3], dt + 64 * s); }
            WG_COMMIT();
        }
        WG_WAIT(0);
#pragma unroll
        for (int i = 0; i < 80; i++) asm volatile("" : "+f"(acc[i]) :: "memory");
        if (tid < 4) {
#pragma unroll
            for (int b = 0; b < 20; b++) ((float2*)(smem + HB + 1024))[4 * b + t] = make_float2(acc[4*b], acc[4*b+1]);
        }
        BAR_SYNC(4, 128);
        const int b = 8 * warp + g, wb = (hb & 2) ? (b < 16 ? b + 4 : b - 16) : b;
        const float2 e = ((const float2*)(smem + HB + 1024))[tid];
        const float h0 = bfr(e.x), h1 = bfr(e.y), m0 = bfr(e.x - h0), m1 = bfr(e.y - h1);
        uint32_t* bp = (uint32_t*)(smem + HB) + wb * 12 + t;
        if (b < 20) { bp[0] = pk_bf(h0, h1); bp[4] = pk_bf(m0, m1); bp[8] = pk_bf(e.x - h0 - m0, e.y - h1 - m1); }
    } else if (warp == 4) {
#pragma unroll 1
        for (int c = 0; c < 9; c++) { mbar_expect_e(BAR(B_FULL + c), 20480); load_chunk(tm_xw, tm_wqt, P.x > P.wq, c, c); }
    } else if (warp == 5) {
        const uint2* wp = (const uint2*)P.wr + lane;
        float s = 0.f;
#pragma unroll
        for (int i = 0; i < 5; i++) if (i < 4 || lane < 16) { const uint2 w = __ldg(wp + 32 * i); s += (bf_lo(w.x) + bf_hi(w.x)) + (bf_lo(w.y) + bf_hi(w.y)); }
#pragma unroll
        for (int d = 1; d < 32; d <<= 1) s += __shfl_xor_sync(~0u, s, d);
        ((float*)(smem + HB + 960))[lane & 15] = s;
    } else if (warp >= 8) {
#pragma unroll
        for (int i = 0; i < 8; i++) ((uint4*)(smem + HZ))[i * 256 + tid - 256] = make_uint4(0, 0, 0, 0);
        PROXY_FENCE_SMEM();
    }
    BAR_SYNC(1, 512);
    if (warp < 2) { const uint4 v = ((const uint4*)(smem + HB))[tid]; st_rlx16(&G->l1.csb[hb][tid], nz(v.x), nz(v.y), nz(v.z), nz(v.w)); }
    if (warp == 0) {
        constexpr int ZB = sizeof(LLScratch) / NHELP;
#pragma unroll 1
        for (int off = 0; off < ZB; off += 32768) bulk_st_e((uint8_t*)&G->ll + hb * ZB + off, sb + HZ, min(32768, ZB - off));
        asm volatile("cp.async.bulk.commit_group;\ncp.async.bulk.wait_group 0;" ::: "memory");
        PROXY_FENCE_GMEM();
    } else {
#pragma unroll 1
        for (int i0 = 0; i0 < 2; i0++) {
            uint4 v[11];
            uint32_t dst[11];
#pragma unroll
            for (int u = 0; u < 11; u++) {
                const int i = min((i0 * 11 + u) * 15 + warp - 1, 323);
                const int un = hb * 18 + i / 18, e = i & 1, cc = ((i % 18) >> 1) * 8 + g;
                const int r = un / 36, hs = (un % 36) / 9, w = un % 9, j = 4 * e + t, h2 = cc / 18;
                const int d = w < 8 ? 18 * (w >> 1) + 8 * (w & 1) + j : 18 * (j >> 1) + 16 + (j & 1);
                dst[u] = h2 * 10368 + (36 * r + 9 * ((hs - r * h2) & 3) + w) * 144 + (cc % 18) * 8 + j;
                v[u] = ld_rlx16((const uint4*)P.wo + (144 * hs + 72 * r + d) * 72 + cc);
            }
#pragma unroll
            for (int u = 0; u < 11; u++) G->wo[dst[u]] = v[u];
        }
    }
    BAR_SYNC(3, 512);
    if (warp != 0) return;
    __threadfence();
    st_rlx4(&G->flag[lane][4 + hb], 1);
    if (hb == 0) {
        poll_counter(&G->cnt[64], NCTA);
        PROXY_FENCE_GMEM();
#pragma unroll 1
        for (int off = 0; off < (int)sizeof(LLFirst); off += 32768) bulk_st_e((uint8_t*)&G->l1 + off, sb + HZ, min(32768, (int)sizeof(LLFirst) - off));
        asm volatile("cp.async.bulk.commit_group;\ncp.async.bulk.wait_group 0;" ::: "memory");
        G->cnt[0] = 0; G->cnt[64] = 0;
    }
}

extern "C" __global__ void __launch_bounds__(NTHR, 1)
fused_block(const __grid_constant__ Params P, const __grid_constant__ CUtensorMap tm_xw,
            const __grid_constant__ CUtensorMap tm_wqt, const __grid_constant__ CUtensorMap tm_gu,
            const __grid_constant__ CUtensorMap tm_xs,
            const __grid_constant__ CUtensorMap tm_d, const __grid_constant__ CUtensorMap tm_o) {
    int tid = threadIdx.x, lane = tid & 31;
    const int warp = __shfl_sync(~0u, tid >> 5, 0);
    const int cta = blockIdx.x - NHELP, qb = cta >> 2, hg = cta & 3;
    int g = lane >> 2, t = lane & 3;
    uint8_t* const misc = smem + SM_MISC;
    const int wg = warp >> 2, wq4 = warp & 3;
    constexpr uint32_t ONE2 = 0x3F803F80u;
    Scratch* const G = P.g;
    if (warp == 0) { TSG(32); TS(0); }
    if (warp == 15) {
        uint32_t c0, c1;
        asm volatile("{\n.reg .u64 a, b;\nmov.u64 a, fused_block_param_0;\ncvt.u64.u32 b, %2;\nadd.u64 a, a, b;\n"
                     "ld.param.u32 %0, [a+-120];\nld.param.u32 %1, [a+64];\n}" : "=r"(c0), "=r"(c1) : "r"(tid >> 10));
        if (cta >= 0) {
            mbar_init_e(BAR(B_W), 1);
            mbar_expect_e(BAR(B_W), 2 * 20736);
            bulk_ld_e(sb + SM_WKV, P.wk, 18432, BAR(B_W));
            bulk_ld_e(sb + SM_WKV + 18432, P.wv, 18432, BAR(B_W));
            bulk_ld_e(sb + SM_MISC + MP_W, P.wk + 9216, 2304, BAR(B_W));
            bulk_ld_e(sb + SM_MISC + MP_W + 2304, P.wv + 9216, 2304, BAR(B_W));
        }
        asm volatile("st.shared.v4.u32 [%0], {%1,%2,%3,%3};" :: "r"(sb + SM_SW), "r"(c0), "r"(c1), "r"(0) : "memory");
    } else if (warp < 11) {
        const int cnt = warp < 7 ? 1 : (warp < 10 ? 4 : 16);
        asm volatile(ELECT "mbarrier.init.shared::cta.b64 [%0], %1;\n@e mbarrier.init.shared::cta.b64 [%0+8], %1;\n"
                     "@e mbarrier.init.shared::cta.b64 [%0+16], %1;\n@e mbarrier.init.shared::cta.b64 [%0+24], %1;\n"
                     "fence.mbarrier_init.release.cluster;\n}" :: "r"(BAR(warp * 4)), "r"(cnt) : "memory");
    }
    BAR_SYNC(0, 512);
    if (cta < 0) { helper(P, &tm_xw, &tm_wqt, warp); return; }
    if (warp == 0) TS(35);

    if (wg == 0) {
        if (warp == 0) {
            const int xi = P.x > P.wq;
            if (lane < 9) asm volatile("mbarrier.arrive.expect_tx.shared::cta.b64 _, [%0], %1;" :: "r"(BAR(B_FULL + lane)), "r"(8192 + 20480) : "memory");
            __syncwarp();
#pragma unroll 1
            for (int c = 0; c < 7; c++) {
                if (c == XAT) {
#pragma unroll 1
                    for (int u = 0; u < 9; u++) tma3d_e(sb + SM_X + u * 8192, &tm_xw, u * 64, qb * 64, xi, BAR(B_FULL + u));
                }
                if (c == 5) BAR_SYNC(8, 320);
                load_chunk(&tm_xw, &tm_wqt, xi, c, c < 2 ? c + 5 : c - 2);
            }
        }
        if (warp == 0) TS(36);
        BAR_SYNC(1, 416);
        float acc[80];
        uint32_t fa[8], fb[8];
        const uint32_t xrow = sb + SM_X + (wq4 * 16 + (lane & 15)) * 128, xs = ((lane >> 4) ^ (lane & 7)) << 4;
        mbar_wait(BAR(B_FULL));
        TS(8);
        ldsm4(fa, xrow + xs); ldsm4(fa + 4, xrow + (xs ^ 32));
#pragma unroll
        for (int c = 0; c < 9; c++) {
            const uint32_t slot = (c < 2 ? c + 5 : c - 2) * 1280;
            const uint64_t db = mkdesc(sb, 8192, 1024, 1) + slot, dt = mkdesc(sb + 16384, 512, 512, 2) + slot;
            WG_FENCE();
            wgp_rs_n32_f32_bf16(acc + 64, fa[0], fa[1], fa[2], fa[3], dt, c); wg_rs_n32_f32_bf16(acc + 64, fa[4], fa[5], fa[6], fa[7], dt + 64);
            wgp_rs_n128_f32_bf16(acc, fa[0], fa[1], fa[2], fa[3], db, c);
            WG_COMMIT();
            WG_WAIT(1);
            if (c) mbar_arrive_e(BAR(B_QC + c - 1));
            ldsm4(fb, xrow + c * 8192 + (xs ^ 64)); ldsm4(fb + 4, xrow + c * 8192 + (xs ^ 96));
            WG_FENCE();
            wg_rs_n128_f32_bf16(acc, fa[4], fa[5], fa[6], fa[7], db + 128);
            WG_COMMIT();
            if (c < 8) mbar_wait(BAR(B_FULL + c + 1));
            WG_FENCE();
            wg_rs_n32_f32_bf16(acc + 64, fb[0], fb[1], fb[2], fb[3], dt + 128); wg_rs_n32_f32_bf16(acc + 64, fb[4], fb[5], fb[6], fb[7], dt + 192);
            wg_rs_n128_f32_bf16(acc, fb[0], fb[1], fb[2], fb[3], db + 256);
            WG_COMMIT();
            WG_WAIT(1);
            if (c < 8) { ldsm4(fa, xrow + (c + 1) * 8192 + xs); ldsm4(fa + 4, xrow + (c + 1) * 8192 + (xs ^ 32)); }
            WG_FENCE();
            wg_rs_n128_f32_bf16(acc, fb[4], fb[5], fb[6], fb[7], db + 384);
            WG_COMMIT();
        }
        TS(34);
        mbar_wait(BAR(B_AUX));
        TS(10);
        const float2 s0 = ((const float2*)(misc + MI_STAT))[wq4 * 16 + g], s1 = ((const float2*)(misc + MI_STAT))[wq4 * 16 + g + 8];
        {
            const uint32_t sel = t == 0 ? 0x3232u : (t == 1 ? 0x4432u : 0x4444u), z = *(volatile uint32_t*)(smem + SM_ZERO);
            const uint32_t m0 = __byte_perm(__float_as_uint(-s0.x), 0, sel), m1 = __byte_perm(__float_as_uint(-s1.x), 0, sel);
            WG_FENCE();
            wg_rs_n128_f32_bf16(acc, m0, m1, z, z, mkdesc(sb + SM_MISC + MP_B, 0, 128, 0) + (hg & 2) * 16);
            wg_rs_n32_f32_bf16(acc + 64, m0, m1, z, z, mkdesc(sb + SM_MISC + MP_B, 0, 128, 0) + ((hg & 2) ? 0 : 128));
            WG_COMMIT();
        }
        WG_WAIT(1);
        mbar_arrive_e(BAR(B_QC + 8));
        const float kq = 0.23570226039551584f * 1.4426950408889634f / 512.0f;
        const float a0 = s0.y * kq, a1 = s1.y * kq;
        const uint32_t qaddr = sb + SM_A + (wq4 * 16 + (lane & 15)) * 304 + (lane >> 4) * 16;
        mbar_wait(BAR(B_QC + 8));
        WG_WAIT(0);
#pragma unroll
        for (int i = 0; i < 80; i++) asm volatile("" : "+f"(acc[i]) :: "memory");
        TS(9);
        const uint32_t qm = qaddr + (hg & 2) * 32 - (hg & 1) * 32, qe = qaddr - ((hg & 2) ? 256 : 0) - (hg & 1) * 32;
        const int skip = (0x8709 >> (4 * hg)) & 15;
#pragma unroll
        for (int s = 0; s < 10; s++) {
            const uint32_t dst = (s == 0 || s > 6) && s == skip ? sb + SM_OHI + tid * 16 : (s < 8 ? qm : qe) + s * 32;
            stsm4(dst, pk_h(acc[8*s] * a0, acc[8*s+1] * a0), pk_h(acc[8*s+2] * a1, acc[8*s+3] * a1),
                       pk_h(acc[8*s+4] * a0, acc[8*s+5] * a0), pk_h(acc[8*s+6] * a1, acc[8*s+7] * a1));
        }
        TS(43);
    } else if (warp < 13) {
        const int wi = warp - 4, R0 = cta * 16;
        const int r = 2 * wi + (lane >> 4), l = lane & 15;
        float4 a;
        {
            const int kp = wi / 3, m = wi % 3;
            const uint4* xp = (const uint4*)(P.x + (R0 + g) * DM + kp * 192) + t;
            uint4 xv[12];
#pragma unroll
            for (int i = 0; i < 12; i++) xv[i] = __ldg(xp + (i >> 1) * 4 + (i & 1) * 8 * 72);
            const bool isv = m == 1 || (m == 2 && (g & 1));
            const int wo = 72 * t + (m < 2 ? g : 8);
            const uint32_t* wp = (const uint32_t*)(smem + SM_WKV) + (isv ? 4608 : 0) + kp * 1728 + wo;
            const uint32_t* wl = kp < 2 ? wp + 1152 : (const uint32_t*)(misc + MP_W) + (isv ? 576 : 0) + wo;
            const uint32_t keep = (m == 2 && g >= 2) ? 0u : ~0u;
            uint32_t wf[48];
            float c1[4] = {0, 0, 0, 0};
            mbar_wait(BAR(B_W));
            if (wi == 0) TS(37);
#pragma unroll
            for (int s = 0; s < 12; s++) {
                const uint32_t* p = (s < 8 ? wp + (s >> 1) * 288 : wl + ((s >> 1) - 4) * 288) + (s & 1) * 36;
                const uint32_t w0 = p[0], w1 = p[9], w2 = p[18], w3 = p[27];
                wf[4*s] = (__byte_perm(w0, w1, 0x5410) & keep) | (ONE2 & ~keep); wf[4*s+1] = __byte_perm(w0, w1, 0x7632);
                wf[4*s+2] = (__byte_perm(w2, w3, 0x5410) & keep) | (ONE2 & ~keep); wf[4*s+3] = __byte_perm(w2, w3, 0x7632);
                mma_bf16(c1, wf[4*s], wf[4*s+1], wf[4*s+2], wf[4*s+3], ONE2, ONE2);
            }
            if (t == 0) *(float2*)(misc + MP_C + kp * 192 + 64 * m + 8 * g) = make_float2(c1[0], c1[2]);
            BAR_ARRIVE(8, 320);
            BAR_SYNC(9, 288);
            if (wi == 0) TS(50);
            const float zf = *(volatile float*)(smem + SM_ZERO);
            float* pk = (float*)(misc + MP_P) + kp * 640;
            const bool wr = m < 2 || g < 2;
            float ac[4][4], gr[4][4];
#pragma unroll
            for (int i = 0; i < 16; i++) { ac[i >> 2][i & 3] = zf; gr[i >> 2][i & 3] = zf; }
#pragma unroll
            for (int i = 0; i < 12; i++) {
                const int j = 8 * (i >> 1);
                mma_bf16(ac[i & 1], wf[j], wf[j+1], wf[j+2], wf[j+3], xv[i].x, xv[i].y);
                mma_bf16(ac[2 + (i & 1)], wf[j+4], wf[j+5], wf[j+6], wf[j+7], xv[i].z, xv[i].w);
            }
            const int gh = (m - kp + 3) % 3;
#pragma unroll
            for (int mm = 1; mm < 3; mm++) {
                if (gh == mm) {
#pragma unroll
                    for (int i = 6 * mm - 6; i < 6 * mm; i++) {
                        mma_bf16_k8(gr[i & 1], xv[i].x, xv[i].y, xv[i].x); mma_bf16_k8(gr[2 + (i & 1)], xv[i].x, xv[i].y, xv[i].y);
                        mma_bf16_k8(gr[i & 1], xv[i].z, xv[i].w, xv[i].z); mma_bf16_k8(gr[2 + (i & 1)], xv[i].z, xv[i].w, xv[i].w);
                    }
                }
            }
#pragma unroll
            for (int n = 0; n < 2; n++) {
                float* d = pk + (8 * n + 2 * t) * 40 + 16 * m + 2 * g;
                const float e0 = ac[n][0] + ac[2+n][0], e1 = ac[n][1] + ac[2+n][1];
                if (wr) { *(float2*)d = make_float2(e0, ac[n][2] + ac[2+n][2]); *(float2*)(d + 40) = make_float2(e1, ac[n][3] + ac[2+n][3]); }
                else if (g == 2) { d[0] = e0; d[40] = e1; }
                if (t == (g >> 1)) pk[(8 * n + g) * 40 + 37 + m] = (g & 1) ? gr[n][1] + gr[2+n][3] : gr[n][0] + gr[2+n][2];
            }
        }
        if (wi == 0) TS(12);
        BAR_SYNC(1, 416);
        if (wi == 0) TS(38);
        if (wi < 8) {
            const float4* pa = (const float4*)(misc + MP_P) + r * 10 + min(l, 9), * pc = (const float4*)(misc + MP_C) + min(l, 8);
            const float4 u0 = pa[0], u1 = pa[160], u2 = pa[320], v0 = pc[0], v1 = pc[12], v2 = pc[24];
            a = make_float4(u0.x + u1.x + u2.x, u0.y + u1.y + u2.y, u0.z + u1.z + u2.z, u0.w + u1.w + u2.w);
            const float4 cs = make_float4(v0.x + v1.x + v2.x, v0.y + v1.y + v2.y, v0.z + v1.z + v2.z, v0.w + v1.w + v2.w);
            const float2 st = ln_stats(__shfl_sync(~0u, a.x, (lane & 16) + 9), __shfl_sync(~0u, a.y + a.z + a.w, (lane & 16) + 9));
            a.x = bfr((a.x - st.x * cs.x) * st.y); a.y = bfr((a.y - st.x * cs.y) * st.y);
            a.z = bfr((a.z - st.x * cs.z) * st.y); a.w = bfr((a.w - st.x * cs.w) * st.y);
            float n2 = a.x * a.x + a.y * a.y;
            const float n8 = __shfl_sync(~0u, n2, (lane & 16) + 8);
            n2 += a.z * a.z + a.w * a.w;
            n2 += __shfl_xor_sync(~0u, n2, 1); n2 += __shfl_xor_sync(~0u, n2, 2);
            if (l == 0) { ((float*)(misc + MP_N2))[r] = n2 + n8; ((float2*)(misc + MP_ST))[r] = st; }
            BAR_ARRIVE(6, 288);
            BAR_SYNC(3, 256);
            if (wi == 0) TS(39);
            const uint32_t mine = ((const uint32_t*)(misc + MP_N2))[r], other = ((const uint32_t*)(misc + MP_N2))[l];
            const uint32_t bal = __ballot_sync(~0u, other > mine || (other == mine && l < r));
            const int rank = __popc((bal >> (lane & 16)) & 0xFFFFu);
            const int blk = (((qb & 1) ? blk_table(MUMASK >> 8) : blk_table(MUMASK)) >> (4 * (rank >> 1))) & 7;
            const int nmu = 2 * ((qb & 1) ? popc8(MUMASK >> 8) : popc8(MUMASK));
            const bool mu = rank < nmu;
            const float ks = mu ? 512.f : (1.f / 512.f), vs = mu ? 128.f : 1.f;
            const float s0 = (l & 4) ? vs : ks, s1 = l < 4 ? ks : vs;
            const uint32_t w0 = nz(pk_h(a.x * s0, a.y * s0)), w1 = nz(pk_h(a.z * s1, a.w * s1));
            uint8_t* stg = misc + MP_STG + blk * 32 + (rank & 1) * 16;
            if (l < 8) {
                uint32_t* d = (uint32_t*)stg + (l < 4 ? (l >> 1) * 64 + (l & 1) * 2 : 188 + l);
                d[0] = w0; d[l < 4 ? 1 : 64] = w1;
            }
            if (l == 8) *(uint4*)(stg + 512) = make_uint4(w0, mu ? 0x5800EA00u : 0x3C002780u, 1u, w1);
            if (l == 9 && (rank == 0 || rank == nmu)) ((uint32_t*)(misc + MP_INFO))[rank != 0] = mine;
            uint32_t vm = max(__float_as_uint(fabsf(a.z)), __float_as_uint(fabsf(a.w)));
            if (l < 8) vm = max(vm, max(__float_as_uint(fabsf(a.x)), __float_as_uint(fabsf(a.y))));
            vm = __reduce_max_sync(~0u, l >= 4 && l < 9 ? vm : 0u);
            ((uint32_t*)(misc + MP_VM))[wi] = vm;
        } else {
            BAR_SYNC(6, 288);
            { const uint4 v = ((const uint4*)(misc + MP_ST))[lane & 7]; st_rlx16_if((uint4*)(G->l1.stat1 + R0) + (lane & 7), nz(v.x), nz(v.y), nz(v.z), nz(v.w), lane < 8); }
#pragma unroll
            for (int i = 0; i < 13; i++) ((uint4*)(misc + (i < 5 ? MP_B : MI_Z - 2560)))[i * 32 + lane] = make_uint4(0, 0, 0, 0);
            delay(DLYS);
            uint4 c0[3];
            ll_load2(3, 32, c0, G->l1.csb[hg] + lane, (const uint4*)(G->l1.stat1 + qb * 64) + lane);
            TS(52);
            ((uint4*)(misc + MP_B))[(lane / 3) * 8 + lane % 3] = c0[0];
            if (lane < 28) ((uint4*)(misc + MP_B))[((lane + 32) / 3) * 8 + (lane + 32) % 3] = c0[1];
            else *(uint32_t*)(smem + SM_SW) = c0[1].x;
            ((uint4*)(misc + MI_STAT))[lane] = c0[2];
            PROXY_FENCE_SMEM();
            __syncwarp();
            mbar_arrive_e(BAR(B_AUX));
            TS(2);
        }
        if (wi < 8) {
            BAR_SYNC(4, 256);
            if (wi == 0) {
                TS(40);
                uint4 kv[3];
#pragma unroll
                for (int it = 0; it < 3; it++) {
                    kv[it] = ((const uint4*)(misc + MP_STG))[lane + 32 * it];
                    if (it < 2 || lane < 16) st_rlx16(&G->l1.kvx[cta][lane + 32 * it], kv[it].x, kv[it].y, kv[it].z, kv[it].w);
                }
                TS(51);
                BAR_ARRIVE(7, 128);
#pragma unroll
                for (int it = 0; it < 3; it++) {
                    const int i = lane + 32 * it;
                    const int b = (i >> 1) & 7;
                    if (i < 80) G->kv[qb * 320 + b * 40 + (i >> 4) * 8 + 2 * ((hg + b) & 3) + (i & 1)] = kv[it];
                }
                const uint32_t vmx = __reduce_max_sync(~0u, ((const uint32_t*)(misc + MP_VM))[lane & 7]);
                if (lane < 3) red_max(&G->l1.info[lane == 1 ? cta >> 4 : 8 + (lane >> 1)], lane < 2 ? ((const uint32_t*)(misc + MP_INFO))[lane] : vmx);
            }
            if (l < 10) G->kvraw[(R0 + r) * 10 + l] = a;
        }
    } else {
        if (warp == 14) {
#pragma unroll 1
            for (int c = 7; c < 9; c++) { mbar_wait(BAR(B_QC + c - 7)); load_chunk(&tm_xw, &tm_wqt, P.x > P.wq, c, c - 2); }
        }
        if (warp == 15 && (uint32_t)__cvta_generic_to_shared(smem_dyn) != sb) __trap();
        if (warp == 13) TS(41);
    }
    const int jrot = cta >> 4;
    if (warp == 4) {
        BAR_SYNC(14, 256);
        red_release_e(&G->cnt[0]);
        TS(13);
    } else if (warp == 12) {
        poll_counter(&G->cnt[0], CNT1);
        PROXY_FENCE_GMEM();
        TS(1);
        mbar_wait(BAR(B_QC + 8));
        const int t1 = (jrot + 1) & 7, t2 = (jrot + 2) & 7, n2 = min(8 - t2, 6);
        mbar_expect_e(BAR(B_KV1), 20480 + 48);
        bulk_ld_e(sb + SM_MISC + MI_KP, G->l1.info, 48, BAR(B_KV1));
        bulk_ld_e(sb + 20480, G->kv + t1 * 1280, 20480, BAR(B_KV1));
        mbar_expect_e(BAR(B_KV2), 6 * 20480);
        bulk_ld_e(sb + 2 * 20480, G->kv + t2 * 1280, n2 * 20480, BAR(B_KV2));
        if (n2 < 6) bulk_ld_e(sb + (2 + n2) * 20480, G->kv, (6 - n2) * 20480, BAR(B_KV2));
    } else if (warp > 4) {
        if (warp < 12) { BAR_ARRIVE(14, 256); } else BAR_SYNC(7, 128);
        delay(DLY0);
        const int w10 = warp - 5 - (warp > 12);
        const uint4* src = G->l1.kvx[jrot * 16] + w10 * 32 + lane;
        uint4 v[4];
        const int e = w10 * 32 + lane, p = e / 80, i = e % 80, b = (i >> 1) & 7;
        ll_load(4, 320, v, src);
        mbar_wait(BAR(B_QC + 2));
#pragma unroll
        for (int j = 0; j < 4; j++) ((uint4*)smem)[j * 320 + b * 40 + (i >> 4) * 8 + 2 * ((p + b) & 3) + (i & 1)] = v[j];
        PROXY_FENCE_SMEM();
        if (warp == 5) TS(42);
    }
    if ((warp & 7) != 4) { BAR_SYNC(5, 448); mbar_arrive_if(BAR(B_KV0), tid == 0); }
    else mbar_wait(BAR(B_KV0));
    if (warp == 0) { TS(11); TSG(60); }

    uint32_t ow[6];
    {
        uint32_t q[8], s[64];
        float o[12];
        load_q(q, wg, tid);
        q[6] = *(volatile uint32_t*)(smem + SM_ZERO); q[7] = *(volatile uint32_t*)(smem + SM_ZERO);
        const uint32_t ca = POLY_CA + q[6];
        uint32_t hold[NHOLD + 1];
#pragma unroll
        for (int i = 0; i < NHOLD; i++) hold[i] = *(volatile uint32_t*)(smem + SM_ZERO);
        uint32_t accor = 0, chk = 1, redo = 0;
        uint32_t jobs = 0x0102u | (warp == 1 ? 0xD000u : (warp == 9 ? 0x3000u : (warp == 13 ? 0x4640u : 0u)));
        uint64_t dk = mkdesc(sb + 20480, 128, 640, 0), dv = mkdesc(sb + 256, 640, 128, 0);
        if (wg) asm volatile("barrier.cta.sync %0, 256;" :: "r"(1 + wg) : "memory");
        WG_FENCE();
        wgz_rs_n256_f16_f16(s, q[0], q[1], q[2], q[3], mkdesc(sb, 128, 640, 0));
        wg_rs_n256_f16_f16(s, q[4], q[5], q[6], q[7], mkdesc(sb + 256, LBO2, 640, 0));
        WG_COMMIT();
        asm volatile("barrier.cta.arrive %0, 256;" :: "r"(1 + ((wg + 1) & 3)) : "memory");
#pragma unroll 1
        for (int it = 0;; it++) {
            if (__builtin_expect(jobs & 1, 0)) {
                if (it == 8) {
                    float l0, l1;
                    if (check_o(o, accor, l0, l1, tid)) redo |= 1;
                    pack_o(o, l0, l1, ow);
                    stage_o(SM_OHI + hg * 9216, ow, tid);
                    __syncwarp();
                    mbar_arrive_if(BAR(B_OHA), ((tid & 31) | (redo & 1)) == 0);
                    accor = 0;
                } else if (it == 1) {
                    const uint32_t* qp = (const uint32_t*)(smem + SM_A + (wq4 * 16 + (tid & 15)) * 304 + (wg + ((tid >> 2) & 4)) * 36);
                    uint32_t n[3] = {0, 0, 0};
#pragma unroll
                    for (int i = 0; i < 9; i++) { const uint32_t a = hfma2(qp[i], 0x60006000u, 0); n[i % 3] = hfma2(a, a, n[i % 3]); }
                    n[0] = hfma2(hfma2(n[0], 0x3C003C00u, n[1]), 0x3C003C00u, n[2]);
                    n[0] = hfma2(n[0] >> 16, 0x3C003C00u, n[0]) & 0xFFFFu;
                    const uint32_t n1 = __reduce_max_sync(~0u, (tid & 16) ? 0u : n[0]), n2 = __reduce_max_sync(~0u, (tid & 16) ? n[0] : 0u);
                    const float kp = ((const float*)(misc + MI_KP))[(tid & 16) ? 8 : (tid + (cta >> 4)) & 7], vm = ((const float*)(misc + MI_KP))[9];
                    const int lim = (kp <= 4096.0f && vm <= 500.0f && vm >= 0.015625f) ? (int)pk_h(fminf(((tid & 16) ? 4090.0f : 221.0f) * frcp(kp), 4090.0f), 0.f) : -1;
                    chk = __ballot_sync(~0u, (int)((tid & 8) ? n2 : n1) > lim);
                    redo = ((chk >> 16) & 1) | ((chk >> 23) & 2);
                    chk >>= 1;
                } else if (warp == 1) {
                    if (it < 15) {
                        tma4d_e(sb + (it - 12) * 23040, &tm_gu, (cta * 36) & ~7, 0, 0, it - 12, BAR(B_GU));
                    } else if (mbar_test(BAR(B_ZOK))) job_load_wo(G, cta, 1);
                    else redo |= 16;
                } else if (warp == 9) {
                    if (it == 12) {
                        mbar_expect_e(BAR(B_FL), 32);
                        bulk_ld_e(sb + SM_MISC + MI_FL, G->flag[qb], 32, BAR(B_FL));
                    } else {
                        mbar_wait(BAR(B_FL));
                        if (__all_sync(~0u, ((const uint32_t*)(misc + MI_FL))[tid & 7] != 0)) job_load_o1(G, cta);
                        else redo |= 8;
                        TS(7);
                    }
                } else {
                    if (it == 6) {
                        bulk_st_e(&G->own[cta], sb + SM_MISC + MI_Z, 4096); bulk_st_e(G->own[cta].o + 1024, sb + SM_MISC + MI_Z, 4096);
                        bulk_st_e(G->own[cta].o + 2048, sb + SM_MISC + MI_Z, 2048);
                        red_relaxed_e(&G->cnt[64]);
                        mbar_expect_e(BAR(B_GU), 4 * 23040);
                        tm_prefetch_e(&tm_gu); tm_prefetch_e(&tm_d); tm_prefetch_e(&tm_xs); tm_prefetch_e(&tm_o);
                        l2_prefetch_e(P.wd + cta * 20736, 41472);
                    } else if (it == 10) {
                        if (!(redo & 4)) job_flag_o1(G, cta);
                    } else {
                        const bool ok = mbar_test(BAR(it == 9 ? B_OHA : B_ZOK));
                        if (!ok) redo |= it == 9 ? 4 : 16;
                        else if (it == 9) job_store_o1(G, cta);
                        else job_load_wo(G, cta, 0);
                    }
                }
            }
            TSL(34 + it);
            if (chk & 1) {
                WG_WAIT(0);
#pragma unroll
                for (int i = 0; i < 64; i++) asm volatile("" : "+r"(s[i]) :: "memory");
                uint32_t a4[4] = {accor, 0, 0, 0};
#pragma unroll
                for (int b = 0; b < 32; b++) if (!((MUMASK >> (b & 15)) & 1)) a4[b >> 3] = __vimax3_u16x2(a4[b >> 3], s[2*b], s[2*b+1]);
                accor = __vimax3_u16x2(__vmaxu2(a4[0], a4[1]), a4[2], a4[3]);
            }
            WG_WAIT(0);
#pragma unroll
            for (int i = 0; i < 64; i++) asm volatile("" : "+r"(s[i]) :: "memory");
#pragma unroll
            for (int h = 0; h < NSPLIT; h++) {
                constexpr int NR = 64 / NSPLIT;
#pragma unroll
                for (int i = h * NR; i < (h + 1) * NR; i++) s[i] = ((MUMASK >> ((i >> 1) & 15)) & 1) ? ex2_mufu(s[i]) : ex2_poly(s[i], ca, i % IMADMOD != IMADMOD - 1);
#pragma unroll
                for (int i = h * NR; i < (h + 1) * NR; i++) asm volatile("" : "+r"(s[i]) :: "memory");
                WG_FENCE();
#pragma unroll
                for (int c = h * NR / 4; c < (h + 1) * NR / 4; c++) {
                    if (c == 0) wgp_rs_n24_f32_f16(o, s[0], s[1], s[2], s[3], dv, it & 7);
                    else wg_rs_n24_f32_f16(o, s[4*c], s[4*c+1], s[4*c+2], s[4*c+3], dv + c * 80);
                }
            }
            WG_COMMIT();
            tid = fresh_tid();
            chk >>= 1; jobs >>= 1;
            if (__builtin_expect((0x8083 >> it) & 1, 0)) {
                if (it == 15) break;
                if (it == 7) load_q(q, 4 + wg, tid); else mbar_wait(BAR(B_KV1 + it));
            }
            asm volatile("barrier.cta.sync %0, 256;" :: "r"(1 + wg) : "memory");
            WG_WAIT(0);
#pragma unroll
            for (int i = 0; i < 12; i++) asm volatile("" : "+f"(o[i]) :: "memory");
            WG_FENCE();
            wgz_rs_n256_f16_f16(s, q[0], q[1], q[2], q[3], dk);
            wg_rs_n256_f16_f16(s, q[4], q[5], q[6], q[7], dk + (mkdesc(256, LBO2, 0, 0) - mkdesc(0, 128, 0, 0)));
            WG_COMMIT();
            asm volatile("barrier.cta.arrive %0, 256;" :: "r"(1 + ((wg + 1) & 3)) : "memory");
            dv = dk + (mkdesc(256, 640, 128, 0) - mkdesc(0, 128, 640, 0));
            dk += it == 6 ? -7 * 1280 : 1280;
        }
        WG_WAIT(0);
#pragma unroll
        for (int i = 0; i < 12; i++) asm volatile("" : "+f"(o[i]) :: "memory");
        if (wq4 == 0) TS(18 + wg);
#pragma unroll
        for (int i = 0; i < NHOLD; i++) accor = __byte_perm(accor, accor, hold[i] ^ 0x3210);
        lane = tid & 31; g = lane >> 2; t = lane & 3;
        const int orow = wq4 * 16 + g;
        float l0, l1;
        if (check_o(o, accor, l0, l1, tid)) redo |= 2;
        pack_o(o, l0, l1, ow);
        if (redo) {
            rare_finish(P, warp, redo);
            if (redo & 2) {
#pragma unroll
                for (int i = 0; i < 6; i++) ow[i] = G->tmp[cta][tid][i];
            }
        }
#pragma unroll
        for (int i = 0; i < 6; i++) ow[i] = nz(ow[i]);
        const uint32_t tw = __shfl_sync(~0u, ow[1], lane | 3);
        mbar_wait(BAR(B_ZOK));
        uint8_t* go = (uint8_t*)G->own[cta].o;
        const uint32_t oa1 = (2 * wg + (t >> 1)) * 1024 + orow * 16 + (t & 1) * 8;
        st_rlx8(go + oa1, ow[2], ow[4]); st_rlx8(go + oa1 + 128, ow[3], ow[5]);
        st_rlx4_if(go + 8192 + wg * 256 + (orow + (t == 2 ? 8 : 0)) * 4, t == 2 ? tw : ow[0], t >= 2);
        mbar_arrive_e(BAR(B_PUB));
        if (wq4 == 0) TS(14 + wg);
    }

    const int orow = wq4 * 16 + g;
    uint32_t wf[92];
    if (wg == 0) {
        float acc[72];
        mbar_arrive_e(BAR(B_END));
        BAR_SYNC(1, 256);
        mbar_wait(BAR(B_PUB));
        stage_o(SM_OLO, ow, tid);
        PROXY_FENCE_SMEM();
        mbar_wait(BAR(B_END));
        mbar_wait(BAR(B_OHT));
        TS(45); TSG(61);
        const uint4* const wo = G->wo + hg * 10368;
#define OPART(S0, N, BASE) do { WG_FENCE(); _Pragma("unroll") for (int s = 0; s < N; s++) { \
            const uint64_t da = mkdesc(sb + (S0 < 18 ? SM_OHI + (S0 + s) * 2048 : SM_OLO + (S0 + s - 18) * 2048), 1024, 128, 0); \
            const uint64_t db = mkdesc(sb + (BASE) + s * 4608, 2304, 128, 0); \
            if (S0 + s == 0) wgz_ss_n144_f32_bf16(acc, da, db); else wg_ss_n144_f32_bf16(acc, da, db); } WG_COMMIT(); } while (0)
        mbar_wait(BAR(B_WF));
        OPART(0, 4, SM_A);
        mbar_wait(BAR(B_WF + 1));
        OPART(4, 6, SM_R);
        WG_WAIT(0);
        mbar_arrive_e(BAR(B_G));
        if (warp == 0) {
            mbar_wait(BAR(B_G));
            mbar_expect_e(BAR(B_WF + 2), 10 * 4608);
            bulk_ld_e(sb + SM_A, wo + 26 * 288, 4 * 4608, BAR(B_WF + 2));
            bulk_ld_e(sb + SM_R, wo + 30 * 288, 6 * 4608, BAR(B_WF + 2));
        }
        mbar_wait(BAR(B_WF + 5));
        OPART(10, 8, 0);
        TS(3);
        WG_WAIT(0);
        mbar_arrive_e(BAR(B_G + 2));
        BAR_SYNC(7, 512);
        TS(22);
        mbar_wait(BAR(B_WF + 6));
        OPART(18, 8, 8 * 4608);
        mbar_wait(BAR(B_WF + 2));
        OPART(26, 4, SM_A);
        OPART(30, 6, SM_R);
        mbar_wait(BAR(B_XS));
        uint32_t wb[20], hw[36];
        const uint32_t xaddr = sb + SM_XS + (wq4 * 16 + (lane & 15)) * 304 + (lane >> 4) * 16;
#pragma unroll
        for (int i = 0; i < 5; i++) ldsm4(wb + 4 * i, sb + ((lane & 7) == 1 ? SM_XS + 64 * 304 : SM_MISC + MI_ONE) + (lane >> 3) * 16 + i * 64);
        ldsm4(hw, xaddr);
        WG_WAIT(0);
#pragma unroll
        for (int i = 0; i < 72; i++) asm volatile("" : "+f"(acc[i]) :: "memory");
        TS(23);
        float sm[4] = {0, 0, 0, 0}, g1[4] = {0, 0, 0, 0}, g2[4] = {0, 0, 0, 0}, g3[4] = {0, 0, 0, 0}, g4[4] = {0, 0, 0, 0};
#pragma unroll
        for (int s = 0; s < 9; s++) {
            uint32_t* x = hw + 4 * s;
            if (s) ldsm4(x, xaddr + s * 32);
#pragma unroll
            for (int i = 0; i < 4; i++) x[i] = add_bf2(x[i], pk_bf(acc[8*s+2*i], acc[8*s+2*i+1]));
            mma_bf16(sm, x[0], x[1], x[2], x[3], wb[2*s], wb[2*s+1]);
            mma_bf16_k8(g1, x[0], x[1], x[0]); mma_bf16_k8(g2, x[0], x[1], x[1]);
            mma_bf16_k8(g3, x[2], x[3], x[2]); mma_bf16_k8(g4, x[2], x[3], x[3]);
        }
        const int dl = (lane & 28) | (g >> 1);
        const float q0 = __shfl_sync(~0u, (g & 1) ? g1[1] + g3[1] : g1[0] + g3[0], dl), q1 = __shfl_sync(~0u, (g & 1) ? g2[3] + g4[3] : g2[2] + g4[2], dl);
        float4* part = G->own[cta].part + orow;
        st_rlx16_if(part, nzf(sm[0]), nzf(q0), nzf(sm[1]), 1u, t == 0);
        st_rlx16_if(part + 8, nzf(sm[2]), nzf(q1), nzf(sm[3]), 1u, t == 0);
        TS(4);
#pragma unroll
        for (int s = 0; s < 9; s++) stsm4(xaddr + s * 32, hw[4*s], hw[4*s+1], hw[4*s+2], hw[4*s+3]);
        if (DLY1) delay(DLY1);
        const float4* pin = G->own[4 * qb + t].part + orow;
        uint4 pp[2];
        ll_load(2, 8, pp, (const uint4*)pin);
        const uint4 p0 = pp[0], p1 = pp[1];
        TS(46);
        if (DNLATE >= 2 && warp == 3) {
            if (DNLATE == 2) tma2d_e(sb + SM_DN0, &tm_d, 0, cta * 36, BAR(B_DN));
            if (DNLATE != 4) tma2d_e(sb + SM_DN1, &tm_d, 192, cta * 36, BAR(B_DN));
            tma2d_e(sb + SM_DN2, &tm_d, 384, cta * 36, BAR(B_DN));
        }
        const bool up = t & 2;
        float v0 = __uint_as_float(up ? p1.x : p0.x) + __shfl_xor_sync(~0u, __uint_as_float(up ? p0.x : p1.x), 2);
        float v1 = __uint_as_float(up ? p1.y : p0.y) + __shfl_xor_sync(~0u, __uint_as_float(up ? p0.y : p1.y), 2);
        float v2 = __uint_as_float(up ? p1.z : p0.z) + __shfl_xor_sync(~0u, __uint_as_float(up ? p0.z : p1.z), 2);
        v0 += __shfl_xor_sync(~0u, v0, 1); v1 += __shfl_xor_sync(~0u, v1, 1); v2 += __shfl_xor_sync(~0u, v2, 1);
        const float2 st = ln_stats(v0, v1);
        uint32_t u = __float_as_uint((v2 - st.x * *(const float*)(smem + SM_SW)) * st.y);
        u ^= ((int)u >> 31) | 0x80000000u;
        const int lr = orow + (t & 2) * 4;
        ((uint32_t*)(misc + MI_CS))[lr] = nz((u & 0xFFFFF800u) | (2047 - (qb * 64 + lr)));
        ((float2*)(misc + MI_STAT))[lr] = st;
        TS(24);
    } else {
        const int tl = tid & 127;
        const uint4* src = (const uint4*)G->own[4 * qb + ((hg + wg) & 3)].o + tl;
        const uint4* srct = src + 512 - (tl & 64);
        const uint32_t wa = sb + wq4 * 23040 + (((lane >> 3) ^ (P.wg > P.wu)) & 1) * 11520 + ((lane >> 4) * 8 + (lane & 7)) * 80 + (wg - 1) * 32;
        uint4 v[5];
        mbar_wait(BAR(B_GU));
        if (wg < 3) {
#pragma unroll
            for (int s = 0; s < 9; s++) ldsm4t(wf + 8 * s + 4, wa + s * 1280 + 16);
        }
#pragma unroll
        for (int s = 0; s < 9; s++) ldsm4t(wf + 8 * s, wa + s * 1280);
        mbar_arrive_if(BAR(B_END) + (wf[64] & *(volatile uint32_t*)(smem + SM_ZERO)), lane == 0);
        mbar_wait(BAR(warp == 15 ? B_END : B_PUB));
        if (warp == 15) {
            TS(44);
            mbar_expect_e(BAR(B_WF + 5), 8 * 4608);
            bulk_ld_e(sb, G->wo + hg * 10368 + 10 * 288, 8 * 4608, BAR(B_WF + 5));
            mbar_expect_e(BAR(B_WF + 6), 8 * 4608);
            bulk_ld_e(sb + 8 * 4608, G->wo + hg * 10368 + 18 * 288, 8 * 4608, BAR(B_WF + 6));
        }
        stage_o(SM_OLO, ow, tid);
        if (DLYO) delay(DLYO);
        ll_load2(5, 128, v, src, srct);
        uint8_t* so = smem + SM_OLO + wg * 9216;
#pragma unroll
        for (int j = 0; j < 4; j++) ((uint4*)so)[tl + j * 128] = v[j];
        if (wq4 < 2) {
            uint32_t* d = (uint32_t*)(so + 8192 + (tl & 15) * 64 + (tl >> 4) * 4);
            d[0] = v[4].x; d[4] = v[4].y; d[8] = v[4].z; d[12] = v[4].w;
        }
        if (warp == 7) {
            ((uint4*)(misc + MI_ONE))[lane] = make_uint4(ONE2, ONE2, ONE2, ONE2);
            ((uint4*)(misc + MI_ACT))[lane] = make_uint4(0, 0, 0, 0); ((uint4*)(misc + MI_ACT + 384))[lane] = make_uint4(0, 0, 0, 0);
        }
        PROXY_FENCE_SMEM();
        BAR_ARRIVE(7, 512);
        if (warp == 4) {
            mbar_wait(BAR(B_G + 2));
            mbar_expect_e(BAR(B_XS), 64 * 304 + 288);
            tma2d_e(sb + SM_XS, &tm_xs, hg * 144, qb * 64, BAR(B_XS));
            bulk_ld_e(sb + SM_XS + 64 * 304, P.wr + hg * 144, 288, BAR(B_XS));
            if (DNLATE == 1) mbar_wait(BAR(B_XS));
            mbar_expect_e(BAR(B_DN), 3 * 14400);
            if (DNLATE != 2) tma2d_e(sb + SM_DN0, &tm_d, 0, cta * 36, BAR(B_DN));
            if (DNLATE < 2 || DNLATE == 4) tma2d_e(sb + SM_DN1, &tm_d, 192, cta * 36, BAR(B_DN));
            if (DNLATE < 2) tma2d_e(sb + SM_DN2, &tm_d, 384, cta * 36, BAR(B_DN));
        }
    }
    BAR_SYNC(10, 512);

    {
        const uint32_t* keys = (const uint32_t*)(misc + MI_CS);
        const uint32_t ka = keys[lane], kb = keys[lane + 32], mine = keys[4 * warp + t];
        const uint4 mk = ((const uint4*)keys)[warp];
        const uint32_t cnt = ((ka > mk.x) + (kb > mk.x)) | ((ka > mk.y) + (kb > mk.y)) << 8 | ((ka > mk.z) + (kb > mk.z)) << 16 | ((ka > mk.w) + (kb > mk.w)) << 24;
        const uint32_t r = (__reduce_add_sync(~0u, cnt) >> (8 * t)) & 0xFF;
        if (r < 8) ((uint32_t*)(misc + MI_TOP))[r] = mine;
    }
    BAR_SYNC(12, 512);
    uint32_t hsw = 0;
    float sgm = 0.f;
    bf16* outp = nullptr;
    if (warp < 8) {
        const int r = 63 - (((const uint32_t*)(misc + MI_TOP))[warp] & 63), lc = min(lane, 17);
        const uint4 v = *(const uint4*)(smem + SM_XS + r * 304 + lc * 16);
        const float2 st = ((const float2*)(misc + MI_STAT))[r];
        const uint32_t m2 = __byte_perm(__float_as_uint(st.x), 0, 0x3232);
        uint32_t* pn = G->ll.hn[qb][warp] + hg * 72 + lc * 4;
        st_rlx16(pn, nz(ln_apply(v.x, m2, st.y)), nz(ln_apply(v.y, m2, st.y)), nz(ln_apply(v.z, m2, st.y)), nz(ln_apply(v.w, m2, st.y)));
        st_rlx16(pn + 32 * 8 * 288, nz(v.x), nz(v.y), nz(v.z), nz(v.w));
    }
    if (wg == 0) {
        const int mat = lane >> 3, r = lane & 7;
        mbar_wait(BAR(B_DN));
#pragma unroll
        for (int i = 0; i < 9; i++) {
            const uint32_t a = sb + (i < 3 ? SM_DN0 : (i < 6 ? SM_DN1 : SM_DN2)) + (3 * warp + i % 3) * 32 + (mat & 1) * 16;
            ldsm4t(wf + 8 * i, a + ((mat >> 1) * 8 + r) * 400); ldsm4t(wf + 8 * i + 4, a + (16 + (mat >> 1) * 8 + r) * 400);
        }
#pragma unroll
        for (int i = 0; i < 5; i++) {
            const int j0 = 2 * i, j1 = min(2 * i + 1, 8);
            const uint32_t a0 = (j0 < 3 ? SM_DN0 : (j0 < 6 ? SM_DN1 : SM_DN2)) + (j0 % 3) * 32, a1 = (j1 < 3 ? SM_DN0 : (j1 < 6 ? SM_DN1 : SM_DN2)) + (j1 % 3) * 32;
            ldsm4t(wf + 72 + 4 * i, sb + ((mat >> 1) ? a1 : a0) + 3 * warp * 32 + (mat & 1) * 16 + (32 + (r & 3)) * 400);
        }
        uint32_t* yp = &G->ll.y[6 * warp][cta][lane];
        TS(5);
        BAR_SYNC(11, 512);
        tma2d_st_e(&tm_o, hg * 144, qb * 64 + wq4 * 16, sb + SM_OUT + wq4 * 4608);
        asm volatile("cp.async.bulk.commit_group;\ncp.async.bulk.wait_group 0;" ::: "memory");
        PROXY_FENCE_GMEM();
        TS(6);
        BAR_SYNC(9, 288);
        TS(28);
        uint32_t b[5];
        ldsm4(b, sb + SM_MISC + MI_ACT + r * 112 + mat * 16);
        b[4] = *(const uint32_t*)(misc + MI_ACT + g * 112 + 64 + t * 4);
        float c[9][4];
#pragma unroll
        for (int i = 0; i < 9; i++) { c[i][0] = 0.f; c[i][1] = 0.f; c[i][2] = 0.f; c[i][3] = 0.f; mma_bf16(c[i], wf[8*i], wf[8*i+1], wf[8*i+2], wf[8*i+3], b[0], b[1]); }
#pragma unroll
        for (int i = 0; i < 9; i++) mma_bf16(c[i], wf[8*i+4], wf[8*i+5], wf[8*i+6], wf[8*i+7], b[2], b[3]);
#pragma unroll
        for (int i = 0; i < 9; i++) {
            mma_bf16_k8(c[i], wf[72+2*i], wf[73+2*i], b[4]);
            st_rlx4(yp + (24 * (i / 3) + 2 * (i % 3)) * NCTA * 32, nz(pk_bf(c[i][0], c[i][1])));
            st_rlx4(yp + (24 * (i / 3) + 2 * (i % 3) + 1) * NCTA * 32, nz(pk_bf(c[i][2], c[i][3])));
        }
        TS(29);
        if (cta < 72) BAR_ARRIVE(13, 512);
    } else {
        if (wg == 1) {
#pragma unroll 3
            for (int it = 0; it < 9; it++) {
                const int i = it * 32 + lane, r = wq4 * 16 + i / 18, c = i % 18;
                const uint4 v = *(const uint4*)(smem + SM_XS + r * 304 + c * 16);
                const float2 st = ((const float2*)(misc + MI_STAT))[r];
                const uint32_t m2 = __byte_perm(__float_as_uint(st.x), 0, 0x3232);
                *(uint4*)(smem + SM_OUT + wq4 * 4608 + i * 16) = make_uint4(add_bf2(v.x, ln_apply(v.x, m2, st.y)), add_bf2(v.y, ln_apply(v.y, m2, st.y)),
                                                                           add_bf2(v.z, ln_apply(v.z, m2, st.y)), add_bf2(v.w, ln_apply(v.w, m2, st.y)));
            }
            PROXY_FENCE_SMEM();
            if (warp == 4) TS(53);
        } else {
            const int w8 = warp - 8;
            const uint4 v = ((const uint4*)(misc + MI_TOP))[tid & 1];
            st_rlx16_if(&G->ll.top[hg * 32 + ((tid & 63) >> 1)][2 * qb + (tid & 1)], v.x, v.y, v.z, v.w, w8 < 2);
            if (w8 == 0) TS(49);
            const uint4* ks = G->ll.top[cta] + 2 * lane;
            delay(DLY2);
            uint4 ab[2];
            ll_load(2, 1, ab, ks);
            if (w8 == 7) TS(25);
            uint32_t l[8] = {ab[0].x, ab[0].y, ab[0].z, ab[0].w, ab[1].x, ab[1].y, ab[1].z, ab[1].w};
            uint32_t key = 0;
#pragma unroll
            for (int r = 0; r < 8; r++) {
                const uint32_t m = __reduce_max_sync(~0u, l[0]);
                if (r == w8) key = m;
                const bool pop = l[0] == m;
#pragma unroll
                for (int i = 0; i < 7 - r; i++) l[i] = pop ? l[i + 1] : l[i];
            }
            const int blk = 31 - ((key >> 6) & 31);
            const uint32_t slot = __shfl_sync(~0u, (ab[0].x > key) + (ab[0].y > key) + (ab[0].z > key) + (ab[0].w > key) + (ab[1].x > key) + (ab[1].y > key) + (ab[1].z > key), blk);
            if (w8 == 7) TS(47);
            uint4 hv[3];
            ll_load(3, 24, hv, (const uint4*)G->ll.hn[blk][slot] + min(lane, 23));
            uint4* hd = (uint4*)(smem + SM_HN + w8 * 1168) + min(lane, 23);
            hd[0] = hv[0]; hd[24] = hv[1]; hd[48] = hv[2];
            ((uint2*)(misc + MI_SEL))[w8] = make_uint2(key, slot);
        }
        const int w12 = warp - 4;
        const uint32_t ha = sb + SM_HN + (lane & 7) * 1168 + wq4 * 288 + (lane >> 3) * 16;
        float4* red = (float4*)(smem + SM_RED) + lane;
        const int f = 8 * (w12 - 7) + g - (cta & 1) * 4;
        BAR_SYNC(11, 512);
        if (warp == 4) TS(26);
        {
            uint32_t b[20];
#pragma unroll
            for (int i = 0; i < 5; i++) ldsm4(b + 4 * i, ha + i * 64);
            float c[4][4];
#pragma unroll
            for (int i = 0; i < 16; i++) c[i >> 2][i & 3] = 0.f;
#pragma unroll
            for (int s = 0; s < 9; s++) {
                mma_bf16(c[s & 1], wf[8*s], wf[8*s+1], wf[8*s+2], wf[8*s+3], b[2*s], b[2*s+1]);
                if (wg < 3) mma_bf16(c[2 + (s & 1)], wf[8*s+4], wf[8*s+5], wf[8*s+6], wf[8*s+7], b[2*s], b[2*s+1]);
            }
            red[wq4 * 160 + (wg - 1) * 64] = make_float4(c[0][0] + c[1][0], c[0][1] + c[1][1], c[0][2] + c[1][2], c[0][3] + c[1][3]);
            if (wg < 3) red[wq4 * 160 + (wg - 1) * 64 + 32] = make_float4(c[2][0] + c[3][0], c[2][1] + c[3][1], c[2][2] + c[3][2], c[2][3] + c[3][3]);
        }
        if (warp == 4) TS(27);
        if (w12 < 7) {
            BAR_ARRIVE(14, 384);
            if (warp < 6 && cta < 72) {
                const int e = tid & 63;
                const uint2 sel = ((const uint2*)(misc + MI_SEL))[e & 7];
                const int tok = 2047 - (sel.x & 2047);
                hsw = ll_load4(G->ll.hs[tok >> 6][sel.y] + cta * 4 + (e >> 4));
                uint32_t u = (sel.x & 0xFFFFF800u) | 0x400u;
                u ^= (~(int)u >> 31) | 0x80000000u;
                sgm = bfr(sigmoidf(bfr(__uint_as_float(u))));
                outp = P.out + tok * DM + cta * 8 + (e >> 3);
                const uint32_t hnw = ((const uint32_t*)(smem + SM_HN + (e & 7) * 1168))[cta * 4 + (e >> 4)];
                hsw = __byte_perm(hsw, hnw, (e & 8) ? 0x7632 : 0x5410);
            }
        } else {
            BAR_SYNC(14, 384);
            red += (w12 - 7) * 32;
            const float4 a = red[0], b = red[160], c = red[320], d = red[480];
            const float g0 = bfr((a.x + b.x) + (c.x + d.x)), g1 = bfr((a.y + b.y) + (c.y + d.y));
            const float u0 = bfr((a.z + b.z) + (c.z + d.z)), u1 = bfr((a.w + b.w) + (c.w + d.w));
            const uint32_t y = pk_bf(bfr(g0 * sigmoidf(g0)) * u0, bfr(g1 * sigmoidf(g1)) * u1);
            if ((uint32_t)f < 36u) {
                uint16_t* act = (uint16_t*)(misc + MI_ACT);
                act[(2 * t) * 56 + f] = y; act[(2 * t + 1) * 56 + f] = y >> 16;
            }
            if (warp == 15) TS(48);
            BAR_ARRIVE(9, 288);
        }
        if (cta < 72) BAR_SYNC(13, 512);
    }
    if (cta < 72) {
        delay(DLY3);
        const uint4* src = (const uint4*)G->ll.y[cta] + tid;
        uint4 vv[2];
        ll_load(2, 512, vv, src);
        const uint4 va = vv[0], vb = vv[1];
        float s[8] = {bf_lo(va.x) + bf_lo(vb.x), bf_hi(va.x) + bf_hi(vb.x), bf_lo(va.y) + bf_lo(vb.y), bf_hi(va.y) + bf_hi(vb.y),
                      bf_lo(va.z) + bf_lo(vb.z), bf_hi(va.z) + bf_hi(vb.z), bf_lo(va.w) + bf_lo(vb.w), bf_hi(va.w) + bf_hi(vb.w)};
        const bool u4 = lane & 16, u2 = lane & 8;
#pragma unroll
        for (int i = 0; i < 4; i++) s[i] = (u4 ? s[i + 4] : s[i]) + __shfl_xor_sync(~0u, u4 ? s[i] : s[i + 4], 16);
#pragma unroll
        for (int i = 0; i < 2; i++) s[i] = (u2 ? s[i + 2] : s[i]) + __shfl_xor_sync(~0u, u2 ? s[i] : s[i + 2], 8);
        *(float2*)(misc + MI_Z + warp * 256 + (lane & 7) * 32 + (lane >> 3) * 8) = make_float2(s[0], s[1]);
        BAR_SYNC(8, 512);
        if (warp == 4) TS(30);
        if (warp == 4 || warp == 5) {
            const int e = tid & 63;
            float y = 0.f;
#pragma unroll
            for (int w = 0; w < 16; w++) y += ((const float*)(misc + MI_Z))[w * 64 + e];
            *outp = __float2bfloat16_rn(bf_lo(hsw) + bfr(bf_hi(hsw) + bfr(bfr(y) * sgm)));
        }
        if (cta == 0 && tid < 256) G->flag[tid >> 3][tid & 7] = 0;
    }
    if (warp == 4) { TS(31); TSG(33); }
    MARK(99999);
}

typedef CUresult (*EncodeFn)(CUtensorMap*, CUtensorMapDataType, cuuint32_t, void*, const cuuint64_t*, const cuuint64_t*,
                             const cuuint32_t*, const cuuint32_t*, CUtensorMapInterleave, CUtensorMapSwizzle,
                             CUtensorMapL2promotion, CUtensorMapFloatOOBfill);

static void make_map(EncodeFn enc, CUtensorMap* tm, const void* p, int cols, int rows, int bc, int br, CUtensorMapSwizzle sw) {
    cuuint64_t gd[2] = {(cuuint64_t)cols, (cuuint64_t)rows}, gs[1] = {(cuuint64_t)cols * 2};
    cuuint32_t bx[2] = {(cuuint32_t)bc, (cuuint32_t)br}, es[2] = {1, 1};
    enc(tm, CU_TENSOR_MAP_DATA_TYPE_BFLOAT16, 2, (void*)p, gd, gs, bx, es, CU_TENSOR_MAP_INTERLEAVE_NONE, sw,
        CU_TENSOR_MAP_L2_PROMOTION_L2_128B, CU_TENSOR_MAP_FLOAT_OOB_FILL_NONE);
}

static void make_pair_map(EncodeFn enc, CUtensorMap* tm, const void* a, const void* b, int cols, int rows, int bc, int br, int bo, int nq, int bq,
                          CUtensorMapSwizzle sw) {
    const char* lo = (const char*)(a > b ? b : a);
    const char* hi = (const char*)(a > b ? a : b);
    cuuint64_t gd[4] = {(cuuint64_t)cols, (cuuint64_t)rows, 2, (cuuint64_t)nq};
    cuuint64_t gs[3] = {(cuuint64_t)cols * 2, (cuuint64_t)(hi - lo), (cuuint64_t)cols * 2 * rows};
    cuuint32_t bx[4] = {(cuuint32_t)bc, (cuuint32_t)br, (cuuint32_t)bo, (cuuint32_t)bq}, es[4] = {1, 1, 1, 1};
    enc(tm, CU_TENSOR_MAP_DATA_TYPE_BFLOAT16, nq ? 4 : 3, (void*)lo, gd, gs, bx, es, CU_TENSOR_MAP_INTERLEAVE_NONE, sw,
        CU_TENSOR_MAP_L2_PROMOTION_L2_128B, CU_TENSOR_MAP_FLOAT_OOB_FILL_NONE);
}

extern "C" void kernel_launch(void* const* d_in, const int* in_sizes, int n_in, void* d_out, int out_size) {
    static EncodeFn enc = nullptr;
    static void* scratch = nullptr;
    if (!enc) {
        void* fn = nullptr;
        cudaDriverEntryPointQueryResult qr;
        cudaGetDriverEntryPoint("cuTensorMapEncodeTiled", &fn, cudaEnableDefault, &qr);
        enc = (EncodeFn)fn;
        cudaGetSymbolAddress(&scratch, g_scratch);
        cudaFuncSetAttribute(fused_block, cudaFuncAttributeMaxDynamicSharedMemorySize, SM_TOTAL);
    }
    Params P;
    P.g = (Scratch*)scratch;
    P.x = (const bf16*)d_in[0]; P.wq = (const bf16*)d_in[1]; P.wk = (const bf16*)d_in[2]; P.wv = (const bf16*)d_in[3];
    P.wo = (const bf16*)d_in[4]; P.wr = (const bf16*)d_in[6]; P.wg = (const bf16*)d_in[7]; P.wu = (const bf16*)d_in[8];
    P.wd = (const bf16*)d_in[9]; P.out = (bf16*)d_out;
    CUtensorMap txw, twqt, tgu, txs, td, to;
    make_pair_map(enc, &txw, P.x, P.wq, DM, SEQ, 64, 64, 1, 0, 0, CU_TENSOR_MAP_SWIZZLE_128B);
    make_pair_map(enc, &tgu, P.wg, P.wu, FF, 144, 40, 144, 2, 4, 2, CU_TENSOR_MAP_SWIZZLE_NONE);
    make_map(enc, &twqt, P.wq, DM, DM, 32, 64, CU_TENSOR_MAP_SWIZZLE_64B);
    make_map(enc, &txs, P.x, DM, SEQ, 152, 64, CU_TENSOR_MAP_SWIZZLE_NONE);
    make_map(enc, &td, P.wd, DM, FF, 200, 36, CU_TENSOR_MAP_SWIZZLE_NONE);
    make_map(enc, &to, P.out, DM, SEQ, 144, 16, CU_TENSOR_MAP_SWIZZLE_NONE);
    fused_block<<<NCTA + NHELP, NTHR, SM_TOTAL, cudaStreamPerThread>>>(P, txw, twqt, tgu, txs, td, to);
}
```
